```python
import torch

def _softmax(x, axis=-1):
    return torch.softmax(x, dim=axis)
def _gelu(x):
    return torch.nn.functional.gelu(x, approximate="tanh")
def _silu(x):
    return torch.nn.functional.silu(x)
def _sigmoid(x):
    return torch.sigmoid(x)
def _layernorm(x, axis=-1, eps=1e-5):
    m = x.mean(dim=axis, keepdim=True)
    v = x.var(dim=axis, keepdim=True, unbiased=False)
    return (x - m) / torch.sqrt(v + eps)
def _scatter_add(tgt, idx, src, axis=0):
    return tgt.clone().index_add_(axis, idx, src)
def _segment_sum(src, seg, n):
    out = torch.zeros((n,) + src.shape[1:], dtype=src.dtype)
    return out.index_add_(0, seg, src)
def _pad(x, pw):
    flat = tuple(v for pair in reversed(pw) for v in pair)
    return torch.nn.functional.pad(x, flat)

kernel_name = 'standalone__sequential_behavior_din__recsys'

def setup_inputs():

    _w = (lambda a: (lambda t: t.to(torch.bfloat16) if t.is_floating_point() else t)(torch.as_tensor(a)))
    B, L, D = 16384, 200, 64
    H = D
    return {
        "target": _w((lambda *s: torch.randn(*s, dtype=torch.bfloat16) * 1.6)(B, D)),
        "hist": _w((lambda *s: torch.randn(*s, dtype=torch.bfloat16) * 1.6)(B, L, D)),
        "mask": _w((lambda lo, hi, *s: torch.randint(lo, hi, s))(0, 2, B, L).to(float)),
        "w1": _w((lambda *s: torch.randn(*s, dtype=torch.bfloat16) * 1.6)(4 * D, H) * (4 * D) ** -0.5),
        "b1": _w((lambda *s: torch.randn(*s, dtype=torch.bfloat16) * 1.6)(H) * 0.1),
        "w2": _w((lambda *s: torch.randn(*s, dtype=torch.bfloat16) * 0.05)(H, 1) * H ** -0.5),
        "b2": _w((lambda *s: torch.randn(*s, dtype=torch.bfloat16) * 0.05)(1) * 0.1),
    }

def reference(target, hist, mask, w1, b1, w2, b2):
    L = hist.shape[1]
    tgt = (lambda x, n, axis: torch.repeat_interleave(x, n, dim=axis))(target[:, None, :], L, axis=1)
    feat = torch.concatenate([hist, tgt, hist - tgt, hist * tgt], axis=-1)
    h = _sigmoid(feat @ w1 + b1)
    scores = (h @ w2 + b2)[..., 0] * mask
    return torch.einsum('bl,bld->bd', scores, hist)
```

```cpp
#include <cuda_runtime.h>
#include <cuda_bf16.h>
#include <stdint.h>

namespace din {

constexpr int kL = 200, kD = 64;
#define NCW 3
#define NSLOT 3
constexpr int CHUNK = 128;
constexpr int NTHREADS = NCW * 128 + 128;
#define PREGS 56
#define CREGS 152
constexpr int PROD_REGS = PREGS, CONS_REGS = CREGS;
#define PF_ROWS 8
#define PF_FAST 10
#define PF_SLOW 2000
#define PF_CYCLES 280
#define RED_SLEEP 40
#define K_SEL 1
#define K_LO 1
#define K_LO2 1
#define K_HI1 2
#define K_HI2 2
#define KL 3
#define KL12 KL
#define NA 5
#define XP 4
#define CHAINS 4
#define PREADD 0
#define OPEN_FROM -100000
#define END_PACE 0
#define PF_EARLY 3
#define TIGHT_ROUNDS 5
constexpr int NSTATIC = 2;
constexpr int S_TGT = CHUNK * 128;
constexpr int S_HDR = S_TGT + 128;
constexpr int S_FULL = S_HDR + 8;
constexpr int S_EMPTY = S_HDR + 16;
constexpr int S_ROW = S_HDR + 24;
constexpr int S_MASK = S_TGT + 256;
constexpr int S_OUT = S_TGT + 1024;
constexpr int SLOT_BYTES = S_OUT + 4096;
constexpr int RING_BYTES_ = NSLOT * SLOT_BYTES;
constexpr int R_PACE = 2 * RING_BYTES_ + S_TGT + 768;
constexpr int R_SPARE = S_HDR + 32;
constexpr int R_STOP = S_HDR + 44;
constexpr int R_LIST = S_TGT + 512;
constexpr int R_VEC = S_TGT + 768;
constexpr int R_SEL = S_TGT + 896;
constexpr int R_CARRY = SLOT_BYTES + S_TGT + 512;
constexpr int R_TGT0 = (NSLOT - 1) * SLOT_BYTES + S_OUT;
constexpr int RING_BYTES = NSLOT * SLOT_BYTES;
constexpr int SMEM_BYTES = NCW * RING_BYTES + 32768 + 1024;
__device__ constexpr int w1_at(int i) { return NCW * RING_BYTES + i * 8192; }
#define LOGT(slot)
static_assert(SMEM_BYTES <= 232448, "shared memory");
constexpr uint32_t H_12 = 2, H_13 = 4, H_14 = 8;
constexpr uint32_t H_GENERAL = 64, H_FINAL = 128, H_SELF = 256, H_NEXT = 0x3ffffc00;
__device__ __forceinline__ uint32_t size_flag(int rows) { return 2u << (max(rows - 89, 0) >> 3); }
constexpr uint32_t ROW_REST = 1u << 30, ROW_MORE = 1u << 31;

__device__ unsigned int g_next;

#define STAMP(k)

#define STR2(x) #x
#define STR(x) STR2(x)
template<int V> struct Int { static constexpr int value = V; };
template<int G> __device__ __forceinline__ void g1_bias(float* d, const uint32_t (&bq)[4], uint32_t loSel);
template<int G> __device__ __forceinline__ void g1_step(float* d, const uint32_t* a, uint32_t loH, uint32_t hiH);
template<> __device__ __forceinline__ void g1_bias<5>(float* d, const uint32_t (&bq)[4], uint32_t loSel) {
  asm volatile("{\n.reg .b64 db;\n.reg .b32 zr;\n"
    "mov.b32 zr, 0;\nmov.b64 db, {%24, zr};\n"
    "wgmma.mma_async.sync.aligned.m64n40k16.f32.bf16.bf16 {%0, %1, %2, %3, %4, %5, %6, %7, %8, %9, %10, %11, %12, %13, %14, %15, %16, %17, %18, %19}, {%20, %21, %22, %23}, db, 0, 1, 1, 0;\n}\n"
    : "=f"(d[0]), "=f"(d[1]), "=f"(d[2]), "=f"(d[3]), "=f"(d[4]), "=f"(d[5]), "=f"(d[6]), "=f"(d[7]), "=f"(d[8]), "=f"(d[9]), "=f"(d[10]), "=f"(d[11]), "=f"(d[12]), "=f"(d[13]), "=f"(d[14]), "=f"(d[15]), "=f"(d[16]), "=f"(d[17]), "=f"(d[18]), "=f"(d[19])
    : "r"(bq[0]), "r"(bq[1]), "r"(bq[2]), "r"(bq[3]), "r"(loSel)
    : "memory");
}
template<> __device__ __forceinline__ void g1_bias<7>(float* d, const uint32_t (&bq)[4], uint32_t loSel) {
  asm volatile("{\n.reg .b64 db;\n.reg .b32 zr;\n"
    "mov.b32 zr, 0;\nmov.b64 db, {%32, zr};\n"
    "wgmma.mma_async.sync.aligned.m64n56k16.f32.bf16.bf16 {%0, %1, %2, %3, %4, %5, %6, %7, %8, %9, %10, %11, %12, %13, %14, %15, %16, %17, %18, %19, %20, %21, %22, %23, %24, %25, %26, %27}, {%28, %29, %30, %31}, db, 0, 1, 1, 0;\n}\n"
    : "=f"(d[0]), "=f"(d[1]), "=f"(d[2]), "=f"(d[3]), "=f"(d[4]), "=f"(d[5]), "=f"(d[6]), "=f"(d[7]), "=f"(d[8]), "=f"(d[9]), "=f"(d[10]), "=f"(d[11]), "=f"(d[12]), "=f"(d[13]), "=f"(d[14]), "=f"(d[15]), "=f"(d[16]), "=f"(d[17]), "=f"(d[18]), "=f"(d[19]), "=f"(d[20]), "=f"(d[21]), "=f"(d[22]), "=f"(d[23]), "=f"(d[24]), "=f"(d[25]), "=f"(d[26]), "=f"(d[27])
    : "r"(bq[0]), "r"(bq[1]), "r"(bq[2]), "r"(bq[3]), "r"(loSel)
    : "memory");
}
template<> __device__ __forceinline__ void g1_bias<8>(float* d, const uint32_t (&bq)[4], uint32_t loSel) {
  asm volatile("{\n.reg .b64 db;\n.reg .b32 zr;\n"
    "mov.b32 zr, 0;\nmov.b64 db, {%36, zr};\n"
    "wgmma.mma_async.sync.aligned.m64n64k16.f32.bf16.bf16 {%0, %1, %2, %3, %4, %5, %6, %7, %8, %9, %10, %11, %12, %13, %14, %15, %16, %17, %18, %19, %20, %21, %22, %23, %24, %25, %26, %27, %28, %29, %30, %31}, {%32, %33, %34, %35}, db, 0, 1, 1, 0;\n}\n"
    : "=f"(d[0]), "=f"(d[1]), "=f"(d[2]), "=f"(d[3]), "=f"(d[4]), "=f"(d[5]), "=f"(d[6]), "=f"(d[7]), "=f"(d[8]), "=f"(d[9]), "=f"(d[10]), "=f"(d[11]), "=f"(d[12]), "=f"(d[13]), "=f"(d[14]), "=f"(d[15]), "=f"(d[16]), "=f"(d[17]), "=f"(d[18]), "=f"(d[19]), "=f"(d[20]), "=f"(d[21]), "=f"(d[22]), "=f"(d[23]), "=f"(d[24]), "=f"(d[25]), "=f"(d[26]), "=f"(d[27]), "=f"(d[28]), "=f"(d[29]), "=f"(d[30]), "=f"(d[31])
    : "r"(bq[0]), "r"(bq[1]), "r"(bq[2]), "r"(bq[3]), "r"(loSel)
    : "memory");
}
template<> __device__ __forceinline__ void g1_bias<9>(float* d, const uint32_t (&bq)[4], uint32_t loSel) {
  asm volatile("{\n.reg .b64 db;\n.reg .b32 zr;\n"
    "mov.b32 zr, 0;\nmov.b64 db, {%40, zr};\n"
    "wgmma.mma_async.sync.aligned.m64n72k16.f32.bf16.bf16 {%0, %1, %2, %3, %4, %5, %6, %7, %8, %9, %10, %11, %12, %13, %14, %15, %16, %17, %18, %19, %20, %21, %22, %23, %24, %25, %26, %27, %28, %29, %30, %31, %32, %33, %34, %35}, {%36, %37, %38, %39}, db, 0, 1, 1, 0;\n}\n"
    : "=f"(d[0]), "=f"(d[1]), "=f"(d[2]), "=f"(d[3]), "=f"(d[4]), "=f"(d[5]), "=f"(d[6]), "=f"(d[7]), "=f"(d[8]), "=f"(d[9]), "=f"(d[10]), "=f"(d[11]), "=f"(d[12]), "=f"(d[13]), "=f"(d[14]), "=f"(d[15]), "=f"(d[16]), "=f"(d[17]), "=f"(d[18]), "=f"(d[19]), "=f"(d[20]), "=f"(d[21]), "=f"(d[22]), "=f"(d[23]), "=f"(d[24]), "=f"(d[25]), "=f"(d[26]), "=f"(d[27]), "=f"(d[28]), "=f"(d[29]), "=f"(d[30]), "=f"(d[31]), "=f"(d[32]), "=f"(d[33]), "=f"(d[34]), "=f"(d[35])
    : "r"(bq[0]), "r"(bq[1]), "r"(bq[2]), "r"(bq[3]), "r"(loSel)
    : "memory");
}
template<> __device__ __forceinline__ void g1_bias<11>(float* d, const uint32_t (&bq)[4], uint32_t loSel) {
  asm volatile("{\n.reg .b64 db;\n.reg .b32 zr;\n"
    "mov.b32 zr, 0;\nmov.b64 db, {%48, zr};\n"
    "wgmma.mma_async.sync.aligned.m64n88k16.f32.bf16.bf16 {%0, %1, %2, %3, %4, %5, %6, %7, %8, %9, %10, %11, %12, %13, %14, %15, %16, %17, %18, %19, %20, %21, %22, %23, %24, %25, %26, %27, %28, %29, %30, %31, %32, %33, %34, %35, %36, %37, %38, %39, %40, %41, %42, %43}, {%44, %45, %46, %47}, db, 0, 1, 1, 0;\n}\n"
    : "=f"(d[0]), "=f"(d[1]), "=f"(d[2]), "=f"(d[3]), "=f"(d[4]), "=f"(d[5]), "=f"(d[6]), "=f"(d[7]), "=f"(d[8]), "=f"(d[9]), "=f"(d[10]), "=f"(d[11]), "=f"(d[12]), "=f"(d[13]), "=f"(d[14]), "=f"(d[15]), "=f"(d[16]), "=f"(d[17]), "=f"(d[18]), "=f"(d[19]), "=f"(d[20]), "=f"(d[21]), "=f"(d[22]), "=f"(d[23]), "=f"(d[24]), "=f"(d[25]), "=f"(d[26]), "=f"(d[27]), "=f"(d[28]), "=f"(d[29]), "=f"(d[30]), "=f"(d[31]), "=f"(d[32]), "=f"(d[33]), "=f"(d[34]), "=f"(d[35]), "=f"(d[36]), "=f"(d[37]), "=f"(d[38]), "=f"(d[39]), "=f"(d[40]), "=f"(d[41]), "=f"(d[42]), "=f"(d[43])
    : "r"(bq[0]), "r"(bq[1]), "r"(bq[2]), "r"(bq[3]), "r"(loSel)
    : "memory");
}
template<> __device__ __forceinline__ void g1_step<5>(float* d, const uint32_t* a, uint32_t loH, uint32_t hiH) {
  asm volatile("{\n.reg .b64 db;\nmov.b64 db, {%24, %25};\n"
    "wgmma.mma_async.sync.aligned.m64n40k16.f32.bf16.bf16 {%0, %1, %2, %3, %4, %5, %6, %7, %8, %9, %10, %11, %12, %13, %14, %15, %16, %17, %18, %19}, {%20, %21, %22, %23}, db, 1, 1, 1, 0;\n}\n"
    : "+f"(d[0]), "+f"(d[1]), "+f"(d[2]), "+f"(d[3]), "+f"(d[4]), "+f"(d[5]), "+f"(d[6]), "+f"(d[7]), "+f"(d[8]), "+f"(d[9]), "+f"(d[10]), "+f"(d[11]), "+f"(d[12]), "+f"(d[13]), "+f"(d[14]), "+f"(d[15]), "+f"(d[16]), "+f"(d[17]), "+f"(d[18]), "+f"(d[19])
    : "r"(a[0]), "r"(a[1]), "r"(a[2]), "r"(a[3]), "r"(loH), "r"(hiH)
    : "memory");
}
template<> __device__ __forceinline__ void g1_step<7>(float* d, const uint32_t* a, uint32_t loH, uint32_t hiH) {
  asm volatile("{\n.reg .b64 db;\nmov.b64 db, {%32, %33};\n"
    "wgmma.mma_async.sync.aligned.m64n56k16.f32.bf16.bf16 {%0, %1, %2, %3, %4, %5, %6, %7, %8, %9, %10, %11, %12, %13, %14, %15, %16, %17, %18, %19, %20, %21, %22, %23, %24, %25, %26, %27}, {%28, %29, %30, %31}, db, 1, 1, 1, 0;\n}\n"
    : "+f"(d[0]), "+f"(d[1]), "+f"(d[2]), "+f"(d[3]), "+f"(d[4]), "+f"(d[5]), "+f"(d[6]), "+f"(d[7]), "+f"(d[8]), "+f"(d[9]), "+f"(d[10]), "+f"(d[11]), "+f"(d[12]), "+f"(d[13]), "+f"(d[14]), "+f"(d[15]), "+f"(d[16]), "+f"(d[17]), "+f"(d[18]), "+f"(d[19]), "+f"(d[20]), "+f"(d[21]), "+f"(d[22]), "+f"(d[23]), "+f"(d[24]), "+f"(d[25]), "+f"(d[26]), "+f"(d[27])
    : "r"(a[0]), "r"(a[1]), "r"(a[2]), "r"(a[3]), "r"(loH), "r"(hiH)
    : "memory");
}
template<> __device__ __forceinline__ void g1_step<8>(float* d, const uint32_t* a, uint32_t loH, uint32_t hiH) {
  asm volatile("{\n.reg .b64 db;\nmov.b64 db, {%36, %37};\n"
    "wgmma.mma_async.sync.aligned.m64n64k16.f32.bf16.bf16 {%0, %1, %2, %3, %4, %5, %6, %7, %8, %9, %10, %11, %12, %13, %14, %15, %16, %17, %18, %19, %20, %21, %22, %23, %24, %25, %26, %27, %28, %29, %30, %31}, {%32, %33, %34, %35}, db, 1, 1, 1, 0;\n}\n"
    : "+f"(d[0]), "+f"(d[1]), "+f"(d[2]), "+f"(d[3]), "+f"(d[4]), "+f"(d[5]), "+f"(d[6]), "+f"(d[7]), "+f"(d[8]), "+f"(d[9]), "+f"(d[10]), "+f"(d[11]), "+f"(d[12]), "+f"(d[13]), "+f"(d[14]), "+f"(d[15]), "+f"(d[16]), "+f"(d[17]), "+f"(d[18]), "+f"(d[19]), "+f"(d[20]), "+f"(d[21]), "+f"(d[22]), "+f"(d[23]), "+f"(d[24]), "+f"(d[25]), "+f"(d[26]), "+f"(d[27]), "+f"(d[28]), "+f"(d[29]), "+f"(d[30]), "+f"(d[31])
    : "r"(a[0]), "r"(a[1]), "r"(a[2]), "r"(a[3]), "r"(loH), "r"(hiH)
    : "memory");
}
template<> __device__ __forceinline__ void g1_step<9>(float* d, const uint32_t* a, uint32_t loH, uint32_t hiH) {
  asm volatile("{\n.reg .b64 db;\nmov.b64 db, {%40, %41};\n"
    "wgmma.mma_async.sync.aligned.m64n72k16.f32.bf16.bf16 {%0, %1, %2, %3, %4, %5, %6, %7, %8, %9, %10, %11, %12, %13, %14, %15, %16, %17, %18, %19, %20, %21, %22, %23, %24, %25, %26, %27, %28, %29, %30, %31, %32, %33, %34, %35}, {%36, %37, %38, %39}, db, 1, 1, 1, 0;\n}\n"
    : "+f"(d[0]), "+f"(d[1]), "+f"(d[2]), "+f"(d[3]), "+f"(d[4]), "+f"(d[5]), "+f"(d[6]), "+f"(d[7]), "+f"(d[8]), "+f"(d[9]), "+f"(d[10]), "+f"(d[11]), "+f"(d[12]), "+f"(d[13]), "+f"(d[14]), "+f"(d[15]), "+f"(d[16]), "+f"(d[17]), "+f"(d[18]), "+f"(d[19]), "+f"(d[20]), "+f"(d[21]), "+f"(d[22]), "+f"(d[23]), "+f"(d[24]), "+f"(d[25]), "+f"(d[26]), "+f"(d[27]), "+f"(d[28]), "+f"(d[29]), "+f"(d[30]), "+f"(d[31]), "+f"(d[32]), "+f"(d[33]), "+f"(d[34]), "+f"(d[35])
    : "r"(a[0]), "r"(a[1]), "r"(a[2]), "r"(a[3]), "r"(loH), "r"(hiH)
    : "memory");
}
template<> __device__ __forceinline__ void g1_step<11>(float* d, const uint32_t* a, uint32_t loH, uint32_t hiH) {
  asm volatile("{\n.reg .b64 db;\nmov.b64 db, {%48, %49};\n"
    "wgmma.mma_async.sync.aligned.m64n88k16.f32.bf16.bf16 {%0, %1, %2, %3, %4, %5, %6, %7, %8, %9, %10, %11, %12, %13, %14, %15, %16, %17, %18, %19, %20, %21, %22, %23, %24, %25, %26, %27, %28, %29, %30, %31, %32, %33, %34, %35, %36, %37, %38, %39, %40, %41, %42, %43}, {%44, %45, %46, %47}, db, 1, 1, 1, 0;\n}\n"
    : "+f"(d[0]), "+f"(d[1]), "+f"(d[2]), "+f"(d[3]), "+f"(d[4]), "+f"(d[5]), "+f"(d[6]), "+f"(d[7]), "+f"(d[8]), "+f"(d[9]), "+f"(d[10]), "+f"(d[11]), "+f"(d[12]), "+f"(d[13]), "+f"(d[14]), "+f"(d[15]), "+f"(d[16]), "+f"(d[17]), "+f"(d[18]), "+f"(d[19]), "+f"(d[20]), "+f"(d[21]), "+f"(d[22]), "+f"(d[23]), "+f"(d[24]), "+f"(d[25]), "+f"(d[26]), "+f"(d[27]), "+f"(d[28]), "+f"(d[29]), "+f"(d[30]), "+f"(d[31]), "+f"(d[32]), "+f"(d[33]), "+f"(d[34]), "+f"(d[35]), "+f"(d[36]), "+f"(d[37]), "+f"(d[38]), "+f"(d[39]), "+f"(d[40]), "+f"(d[41]), "+f"(d[42]), "+f"(d[43])
    : "r"(a[0]), "r"(a[1]), "r"(a[2]), "r"(a[3]), "r"(loH), "r"(hiH)
    : "memory");
}
__device__ __forceinline__ void g2_first(float (&o)[16], const uint32_t* a, uint32_t loH, uint32_t meta, uint32_t hiH) {
  asm volatile("{\n.reg .b64 db;\nmov.b64 db, {%20, %22};\n"
    "wgmma.mma_async.sp.sync.aligned.m64n32k32.f32.bf16.bf16 {%0, %1, %2, %3, %4, %5, %6, %7, %8, %9, %10, %11, %12, %13, %14, %15}, {%16, %17, %18, %19}, db, %21, 0, 0, 1, 1, 1;\n}\n"
    : "=f"(o[0]), "=f"(o[1]), "=f"(o[2]), "=f"(o[3]), "=f"(o[4]), "=f"(o[5]), "=f"(o[6]), "=f"(o[7]), "=f"(o[8]), "=f"(o[9]), "=f"(o[10]), "=f"(o[11]), "=f"(o[12]), "=f"(o[13]), "=f"(o[14]), "=f"(o[15])
    : "r"(a[0]), "r"(a[1]), "r"(a[2]), "r"(a[3]), "r"(loH), "r"(meta), "r"(hiH)
    : "memory");
}
__device__ __forceinline__ void g2_more(float (&o)[16], const uint32_t* a, uint32_t loH, uint32_t meta, uint32_t hiH) {
  asm volatile("{\n.reg .b64 db;\nmov.b64 db, {%20, %22};\n"
    "wgmma.mma_async.sp.sync.aligned.m64n32k32.f32.bf16.bf16 {%0, %1, %2, %3, %4, %5, %6, %7, %8, %9, %10, %11, %12, %13, %14, %15}, {%16, %17, %18, %19}, db, %21, 0, 1, 1, 1, 1;\n}\n"
    : "+f"(o[0]), "+f"(o[1]), "+f"(o[2]), "+f"(o[3]), "+f"(o[4]), "+f"(o[5]), "+f"(o[6]), "+f"(o[7]), "+f"(o[8]), "+f"(o[9]), "+f"(o[10]), "+f"(o[11]), "+f"(o[12]), "+f"(o[13]), "+f"(o[14]), "+f"(o[15])
    : "r"(a[0]), "r"(a[1]), "r"(a[2]), "r"(a[3]), "r"(loH), "r"(meta), "r"(hiH)
    : "memory");
}
template<int N> __device__ __forceinline__ void mma_wait(float* d, Int<4>) {
  asm volatile("wgmma.wait_group.sync.aligned %16;"
    : "+f"(d[0]), "+f"(d[1]), "+f"(d[2]), "+f"(d[3]), "+f"(d[4]), "+f"(d[5]), "+f"(d[6]), "+f"(d[7]), "+f"(d[8]), "+f"(d[9]), "+f"(d[10]), "+f"(d[11]), "+f"(d[12]), "+f"(d[13]), "+f"(d[14]), "+f"(d[15])
    : "n"(N) : "memory");
}
template<int N> __device__ __forceinline__ void mma_wait(float* d, Int<5>) {
  asm volatile("wgmma.wait_group.sync.aligned %20;"
    : "+f"(d[0]), "+f"(d[1]), "+f"(d[2]), "+f"(d[3]), "+f"(d[4]), "+f"(d[5]), "+f"(d[6]), "+f"(d[7]), "+f"(d[8]), "+f"(d[9]), "+f"(d[10]), "+f"(d[11]), "+f"(d[12]), "+f"(d[13]), "+f"(d[14]), "+f"(d[15]), "+f"(d[16]), "+f"(d[17]), "+f"(d[18]), "+f"(d[19])
    : "n"(N) : "memory");
}
template<int N> __device__ __forceinline__ void mma_wait(float* d, Int<7>) {
  asm volatile("wgmma.wait_group.sync.aligned %28;"
    : "+f"(d[0]), "+f"(d[1]), "+f"(d[2]), "+f"(d[3]), "+f"(d[4]), "+f"(d[5]), "+f"(d[6]), "+f"(d[7]), "+f"(d[8]), "+f"(d[9]), "+f"(d[10]), "+f"(d[11]), "+f"(d[12]), "+f"(d[13]), "+f"(d[14]), "+f"(d[15]), "+f"(d[16]), "+f"(d[17]), "+f"(d[18]), "+f"(d[19]), "+f"(d[20]), "+f"(d[21]), "+f"(d[22]), "+f"(d[23]), "+f"(d[24]), "+f"(d[25]), "+f"(d[26]), "+f"(d[27])
    : "n"(N) : "memory");
}
template<int N> __device__ __forceinline__ void mma_wait(float* d, Int<8>) {
  asm volatile("wgmma.wait_group.sync.aligned %32;"
    : "+f"(d[0]), "+f"(d[1]), "+f"(d[2]), "+f"(d[3]), "+f"(d[4]), "+f"(d[5]), "+f"(d[6]), "+f"(d[7]), "+f"(d[8]), "+f"(d[9]), "+f"(d[10]), "+f"(d[11]), "+f"(d[12]), "+f"(d[13]), "+f"(d[14]), "+f"(d[15]), "+f"(d[16]), "+f"(d[17]), "+f"(d[18]), "+f"(d[19]), "+f"(d[20]), "+f"(d[21]), "+f"(d[22]), "+f"(d[23]), "+f"(d[24]), "+f"(d[25]), "+f"(d[26]), "+f"(d[27]), "+f"(d[28]), "+f"(d[29]), "+f"(d[30]), "+f"(d[31])
    : "n"(N) : "memory");
}
template<int N> __device__ __forceinline__ void mma_wait(float* d, Int<9>) {
  asm volatile("wgmma.wait_group.sync.aligned %36;"
    : "+f"(d[0]), "+f"(d[1]), "+f"(d[2]), "+f"(d[3]), "+f"(d[4]), "+f"(d[5]), "+f"(d[6]), "+f"(d[7]), "+f"(d[8]), "+f"(d[9]), "+f"(d[10]), "+f"(d[11]), "+f"(d[12]), "+f"(d[13]), "+f"(d[14]), "+f"(d[15]), "+f"(d[16]), "+f"(d[17]), "+f"(d[18]), "+f"(d[19]), "+f"(d[20]), "+f"(d[21]), "+f"(d[22]), "+f"(d[23]), "+f"(d[24]), "+f"(d[25]), "+f"(d[26]), "+f"(d[27]), "+f"(d[28]), "+f"(d[29]), "+f"(d[30]), "+f"(d[31]), "+f"(d[32]), "+f"(d[33]), "+f"(d[34]), "+f"(d[35])
    : "n"(N) : "memory");
}
template<int N> __device__ __forceinline__ void mma_wait(float* d, Int<11>) {
  asm volatile("wgmma.wait_group.sync.aligned %44;"
    : "+f"(d[0]), "+f"(d[1]), "+f"(d[2]), "+f"(d[3]), "+f"(d[4]), "+f"(d[5]), "+f"(d[6]), "+f"(d[7]), "+f"(d[8]), "+f"(d[9]), "+f"(d[10]), "+f"(d[11]), "+f"(d[12]), "+f"(d[13]), "+f"(d[14]), "+f"(d[15]), "+f"(d[16]), "+f"(d[17]), "+f"(d[18]), "+f"(d[19]), "+f"(d[20]), "+f"(d[21]), "+f"(d[22]), "+f"(d[23]), "+f"(d[24]), "+f"(d[25]), "+f"(d[26]), "+f"(d[27]), "+f"(d[28]), "+f"(d[29]), "+f"(d[30]), "+f"(d[31]), "+f"(d[32]), "+f"(d[33]), "+f"(d[34]), "+f"(d[35]), "+f"(d[36]), "+f"(d[37]), "+f"(d[38]), "+f"(d[39]), "+f"(d[40]), "+f"(d[41]), "+f"(d[42]), "+f"(d[43])
    : "n"(N) : "memory");
}

__device__ __forceinline__ uint32_t smem_u32(const void* p) { return (uint32_t)__cvta_generic_to_shared(p); }

__device__ __forceinline__ void mbar_init(uint32_t bar, uint32_t cnt) {
  asm volatile("mbarrier.init.shared::cta.b64 [%0], %1;" :: "r"(bar), "r"(cnt) : "memory");
}
__device__ __forceinline__ void mbar_arrive(uint32_t bar) {
  asm volatile("mbarrier.arrive.shared::cta.b64 _, [%0];" :: "r"(bar) : "memory");
}
__device__ __forceinline__ void mbar_wait(uint32_t bar, uint32_t parity) {
  asm volatile("{\n.reg .pred p;\n.reg .u32 n;\n"
               "mov.u32 n, 0;\n"
               "WAIT_LOOP:\n"
               "mbarrier.try_wait.parity.shared::cta.b64 p, [%0], %1;\n"
               "@p bra.uni WAIT_DONE;\n"
               "add.u32 n, n, 1;\n"
               "setp.lt.u32 p, n, 0x1000000;\n"
               "@p bra.uni WAIT_LOOP;\n"
               "trap;\n"
               "WAIT_DONE:\n}\n"
               :: "r"(bar), "r"(parity) : "memory");
}
__device__ __forceinline__ uint32_t mbar_test(uint32_t bar, uint32_t parity) {
  uint32_t ok;
  asm volatile("{\n.reg .pred p;\nmbarrier.test_wait.parity.shared::cta.b64 p, [%1], %2;\nselp.u32 %0, 1, 0, p;\n}\n"
               : "=r"(ok) : "r"(bar), "r"(parity) : "memory");
  return ok;
}
__device__ __forceinline__ void cp_async16(uint32_t dst, const void* src) {
  asm volatile("cp.async.cg.shared.global [%0], [%1], 16;" :: "r"(dst), "l"(src) : "memory");
}
#define DIN_ADDR4                                                                        \
  "mov.b64 {x, y}, %0;\ndp4a.u32.u32 x, %8, 0x80, %11;\nmov.b64 %0, {x, y};\n"           \
  "mov.b64 {x, y}, %1;\ndp4a.u32.u32 x, %8, 0x8000, %11;\nmov.b64 %1, {x, y};\n"         \
  "mov.b64 {x, y}, %2;\ndp4a.u32.u32 x, %8, 0x800000, %11;\nmov.b64 %2, {x, y};\n"       \
  "mov.b64 {x, y}, %3;\ndp4a.u32.u32 x, %8, 0x80000000, %11;\nmov.b64 %3, {x, y};\n"
template<int T>
__device__ __forceinline__ void cp_group(const uint32_t (&dst)[4], uint64_t (&a)[4], uint32_t rows4, uint32_t base, uint64_t pol) {
  asm volatile("{\n.reg .u32 x, y;\n" DIN_ADDR4
               "cp.async.cg.shared.global.L2::cache_hint [%4 + %10], [%0], 16, %9;\n"
               "cp.async.cg.shared.global.L2::cache_hint [%5 + %10], [%1], 16, %9;\n"
               "cp.async.cg.shared.global.L2::cache_hint [%6 + %10], [%2], 16, %9;\n"
               "cp.async.cg.shared.global.L2::cache_hint [%7 + %10], [%3], 16, %9;\n}\n"
               : "+l"(a[0]), "+l"(a[1]), "+l"(a[2]), "+l"(a[3])
               : "r"(dst[0]), "r"(dst[1]), "r"(dst[2]), "r"(dst[3]), "r"(rows4), "l"(pol), "n"(T * 2048), "r"(base) : "memory");
}
template<int T>
__device__ __forceinline__ void cp_group_z(const uint32_t (&dst)[4], uint64_t (&a)[4], uint32_t rows4, uint32_t base, int left, uint64_t pol) {
  asm volatile("{\n.reg .u32 x, y;\n.reg .pred p0, p1, p2, p3;\n" DIN_ADDR4
               "setp.le.s32 p0, %12, %13;\nsetp.le.s32 p1, %12, %13 + 1;\nsetp.le.s32 p2, %12, %13 + 2;\nsetp.le.s32 p3, %12, %13 + 3;\n"
               "cp.async.cg.shared.global.L2::cache_hint [%4 + %10], [%0], 16, p0, %9;\n"
               "cp.async.cg.shared.global.L2::cache_hint [%5 + %10], [%1], 16, p1, %9;\n"
               "cp.async.cg.shared.global.L2::cache_hint [%6 + %10], [%2], 16, p2, %9;\n"
               "cp.async.cg.shared.global.L2::cache_hint [%7 + %10], [%3], 16, p3, %9;\n}\n"
               : "+l"(a[0]), "+l"(a[1]), "+l"(a[2]), "+l"(a[3])
               : "r"(dst[0]), "r"(dst[1]), "r"(dst[2]), "r"(dst[3]), "r"(rows4), "l"(pol), "n"(T * 2048), "r"(base),
                 "r"(left), "n"(T * 16) : "memory");
}
__device__ __forceinline__ uint32_t prmt(uint32_t a, uint32_t b, uint32_t sel) {
  uint32_t d;
  asm("prmt.b32 %0, %1, %2, %3;" : "=r"(d) : "r"(a), "r"(b), "r"(sel));
  return d;
}
__device__ __forceinline__ uint32_t ballot_bit(uint32_t x, uint32_t bit) {
  uint32_t d;
  asm volatile("{\n.reg .pred p;\n.reg .u32 t;\nand.b32 t, %1, %2;\nsetp.ne.u32 p, t, 0;\nvote.sync.ballot.b32 %0, p, 0xffffffff;\n}\n"
               : "=r"(d) : "r"(x), "r"(bit));
  return d;
}
__device__ __forceinline__ uint4 load_mask(const void* mask, uint32_t b, uint32_t i) {
  uint4 m;
  asm volatile("ld.global.nc.L1::no_allocate.v4.u32 {%0,%1,%2,%3}, [%4];"
               : "=r"(m.x), "=r"(m.y), "=r"(m.z), "=r"(m.w) : "l"(reinterpret_cast<const uint4*>(mask) + (b * 25u + i)));
  return m;
}
__device__ __forceinline__ uint32_t nonzero_as_one(uint32_t x) {
  uint32_t d;
  asm("set.neu.bf16x2.bf16x2 %0, %1, %2;" : "=r"(d) : "r"(x), "r"(0u));
  return d;
}
__device__ __forceinline__ void cp_async_arrive_noinc(uint32_t bar) {
  asm volatile("cp.async.mbarrier.arrive.noinc.shared::cta.b64 [%0];" :: "r"(bar) : "memory");
}
__device__ __forceinline__ void ldsm_x4(uint32_t addr, uint32_t& r0, uint32_t& r1, uint32_t& r2, uint32_t& r3) {
  asm volatile("ldmatrix.sync.aligned.m8n8.x4.shared.b16 {%0,%1,%2,%3}, [%4];"
               : "=r"(r0), "=r"(r1), "=r"(r2), "=r"(r3) : "r"(addr) : "memory");
}
__device__ __forceinline__ void ldsm_x4_t(uint32_t addr, uint32_t& r0, uint32_t& r1, uint32_t& r2, uint32_t& r3) {
  asm volatile("ldmatrix.sync.aligned.m8n8.x4.trans.shared.b16 {%0,%1,%2,%3}, [%4];"
               : "=r"(r0), "=r"(r1), "=r"(r2), "=r"(r3) : "r"(addr) : "memory");
}
__device__ __forceinline__ void stsm_x4_t(uint32_t addr, uint32_t r0, uint32_t r1, uint32_t r2, uint32_t r3) {
  asm volatile("stmatrix.sync.aligned.m8n8.x4.trans.shared.b16 [%0], {%1,%2,%3,%4};"
               :: "r"(addr), "r"(r0), "r"(r1), "r"(r2), "r"(r3) : "memory");
}
__device__ __forceinline__ uint32_t hfma2_bf16(uint32_t a, uint32_t b, uint32_t c) {
  uint32_t d;
  asm volatile("fma.rn.bf16x2 %0, %1, %2, %3;" : "=r"(d) : "r"(a), "r"(b), "r"(c));
  return d;
}
__device__ __forceinline__ uint32_t pack_bf16(float lo, float hi) {
  uint32_t d;
  asm("cvt.rn.bf16x2.f32 %0, %1, %2;" : "=r"(d) : "f"(hi), "f"(lo));
  return d;
}
__device__ __forceinline__ uint32_t lds32(uint32_t a) {
  uint32_t v; asm volatile("ld.shared.u32 %0, [%1];" : "=r"(v) : "r"(a) : "memory"); return v;
}
__device__ __forceinline__ uint32_t lds16(uint32_t a) {
  uint32_t v; asm volatile("ld.shared.u16 %0, [%1];" : "=r"(v) : "r"(a) : "memory"); return v;
}
__device__ __forceinline__ void sts32(uint32_t a, uint32_t v) {
  asm volatile("st.shared.u32 [%0], %1;" :: "r"(a), "r"(v) : "memory");
}
__device__ __forceinline__ void sts16(uint32_t a, uint32_t v) {
  asm volatile("st.shared.u16 [%0], %1;" :: "r"(a), "h"((unsigned short)v) : "memory");
}
__device__ __forceinline__ void sts8(uint32_t a, uint32_t v) {
  asm volatile("st.shared.u8 [%0], %1;" :: "r"(a), "r"(v) : "memory");
}
constexpr uint32_t DESC_ROWS = 0x40000040u, DESC_HALVES = 0x80000020u;
__device__ __forceinline__ uint32_t desc_lo(uint32_t addr) { return ((addr & 0x3FFFF) >> 4) | (1u << 16); }

__device__ __forceinline__ uint4 lds128(uint32_t a) {
  uint4 v;
  asm volatile("ld.shared.v4.u32 {%0,%1,%2,%3}, [%4];" : "=r"(v.x), "=r"(v.y), "=r"(v.z), "=r"(v.w) : "r"(a) : "memory");
  return v;
}
__device__ __forceinline__ void sts128(uint32_t a, uint4 v) {
  asm volatile("st.shared.v4.u32 [%0], {%1,%2,%3,%4};" :: "r"(a), "r"(v.x), "r"(v.y), "r"(v.z), "r"(v.w) : "memory");
}
__device__ __forceinline__ void prefetch_l2(const void* p, uint32_t bytes) {
  asm volatile("cp.async.bulk.prefetch.L2.global [%0], %1;" :: "l"(p), "r"(bytes) : "memory");
}

__device__ __forceinline__ void mma_fence() { asm volatile("wgmma.fence.sync.aligned;" ::: "memory"); }
__device__ __forceinline__ void mma_commit() { asm volatile("wgmma.commit_group.sync.aligned;" ::: "memory"); }
template<bool FIRST>
__device__ __forceinline__ void hmma(float (&c)[4], const uint32_t* a, uint32_t b0, uint32_t b1) {
  if (FIRST)
    asm volatile("mma.sync.aligned.m16n8k16.row.col.f32.bf16.bf16.f32 {%0,%1,%2,%3}, {%4,%5,%6,%7}, {%8,%9}, {%10,%10,%10,%10};"
                 : "=f"(c[0]), "=f"(c[1]), "=f"(c[2]), "=f"(c[3]) : "r"(a[0]), "r"(a[1]), "r"(a[2]), "r"(a[3]), "r"(b0), "r"(b1), "f"(0.f));
  else
    asm volatile("mma.sync.aligned.m16n8k16.row.col.f32.bf16.bf16.f32 {%0,%1,%2,%3}, {%4,%5,%6,%7}, {%8,%9}, {%0,%1,%2,%3};"
                 : "+f"(c[0]), "+f"(c[1]), "+f"(c[2]), "+f"(c[3]) : "r"(a[0]), "r"(a[1]), "r"(a[2]), "r"(a[3]), "r"(b0), "r"(b1));
}
__device__ __forceinline__ void tanh_some(float* d, int i0, int i1) {
#pragma unroll
  for (int i = i0; i < i1; i++) asm volatile("tanh.approx.f32 %0, %0;" : "+f"(d[i ^ 2]));
}
__device__ __forceinline__ uint32_t mix(const float* d, int i, float w2a, float w2b, float c32) {
  uint32_t p;
  asm volatile("{\n.reg .f32 x, y;\nfma.rn.f32 x, %3, %6, %7;\nfma.rn.f32 y, %4, %6, %7;\n"
               "fma.rn.f32 x, %1, %5, x;\nfma.rn.f32 y, %2, %5, y;\ncvt.rn.bf16x2.f32 %0, y, x;\n}\n"
               : "=r"(p) : "f"(d[4 * i]), "f"(d[4 * i + 1]), "f"(d[4 * i + 2]), "f"(d[4 * i + 3]), "f"(w2a), "f"(w2b), "f"(c32));
  return p;
}
__device__ __forceinline__ uint32_t sums_at(uint32_t lane, uint32_t step) {
  const uint32_t d = (lane & 7) * 2 + ((lane >> 3) & 1);
  return S_OUT + (lane >> 4) * step + (d ^ (d >> 3)) * 16;
}
template<int K> __device__ __forceinline__ uint32_t keep(uint32_t x) { return K ? __shfl_sync(0xffffffffu, x, 0) : x; }

__global__ void __launch_bounds__(NTHREADS, 1)
din_kernel(const __nv_bfloat16* __restrict__ mask, const __nv_bfloat16* __restrict__ target, int B, int grid,
           uint32_t pf_mask, uint32_t pf_tgt, const __nv_bfloat16* __restrict__ w1, const __nv_bfloat16* __restrict__ hist,
           const __nv_bfloat16* __restrict__ b1, const __nv_bfloat16* __restrict__ w2,
           const __nv_bfloat16* __restrict__ b2, __nv_bfloat16* __restrict__ out, unsigned int* counter, int pace,
           int tight_from) {
  {
    const char* pm = reinterpret_cast<const char*>(mask) + (size_t)blockIdx.x * pf_mask;
    const char* pt = reinterpret_cast<const char*>(target) + (size_t)blockIdx.x * pf_tgt;
    const uint32_t o = threadIdx.x * 128;
    asm volatile("{\n.reg .pred p;\nsetp.lt.u32 p, %1, %2;\n@p prefetch.global.L2 [%0];\n}\n" :: "l"(pm + o), "r"(o), "r"(pf_mask));
    asm volatile("{\n.reg .pred p;\nsetp.lt.u32 p, %1, %2;\n@p prefetch.global.L2 [%0];\n}\n" :: "l"(pt + o), "r"(o), "r"(pf_tgt));
  }
  extern __shared__ unsigned char smem_raw[];
  const uint32_t sb = (smem_u32(smem_raw) + 1023u) & ~1023u;
  const int tid = threadIdx.x, lane = tid & 31;
  const int warp = __shfl_sync(0xffffffffu, tid >> 5, 0);
#define ACT NCW
  const int bstep = ACT * grid;

  STAMP(0);
  if (warp < NCW * 4) {
    const int wg = warp >> 2, w = warp & 3;
    const int g = lane >> 2;
    const uint32_t ring = sb + wg * RING_BYTES;
    const bool active = wg * grid + (int)blockIdx.x < B && wg < ACT;
    {
      const int t = tid & 127;
      const uint32_t dst = sb + ((t ^ ((t >> 3) & 7)) << 4);
      const char* src = reinterpret_cast<const char*>(w1) + t * 16;
#pragma unroll
      for (int i = 0; i < 4; i++) cp_async16(dst + w1_at(i) + wg * 2048, src + i * 8192 + wg * 2048);
      cp_async16(dst + w1_at(0) + wg * 8192 + 6144, src + wg * 8192 + 6144);
      if (wg == 0) cp_async16(dst + w1_at(3) + 6144, src + 3 * 8192 + 6144);
      if (lane < 8) {
        if (w == 0 && active) cp_async16(ring + R_TGT0 + lane * 16, target + (size_t)(wg * grid + blockIdx.x) * kD + lane * 8);
        if (w == 1 && wg < 2) cp_async16(ring + R_VEC + lane * 16, (wg ? w2 : b1) + lane * 8);
      }
    }
    if (w == 2) sts32(ring + R_SEL + lane * 4, 0x3e803e80u);
    uint32_t rb2;
    asm volatile("ld.global.nc.u16 %0, [%1];" : "=r"(rb2) : "l"(b2));
    asm volatile("setmaxnreg.inc.sync.aligned.u32 %0;" :: "n"(CONS_REGS));
    asm volatile("cp.async.wait_all;" ::: "memory");
    STAMP(5);
    asm volatile("bar.sync 1, %0;" :: "n"(NCW * 160) : "memory");
    const uint32_t half2 = 0x3f003f00u, nhalf2 = 0xbf00bf00u, nzero2 = 0x80008000u;
    const uint32_t vec = sb + R_VEC + (16 * w + g) * 2;
    const float w2a = 0.5f * __uint_as_float(lds16(vec + RING_BYTES) << 16);
    const float w2b = 0.5f * __uint_as_float(lds16(vec + RING_BYTES + 16) << 16);
    const uint32_t rw2 = lds32(sb + RING_BYTES + R_VEC + lane * 4);
    float c32 = __uint_as_float(rw2 << 16) + __uint_as_float(rw2 & 0xffff0000u);
#pragma unroll
    for (int o = 16; o; o >>= 1) c32 += __shfl_xor_sync(0xffffffffu, c32, o);
    c32 = (0.5f * c32 + __uint_as_float(rb2 << 16)) * (1.0f / 32.0f);
    const float b1a = 0.5f * __uint_as_float(lds16(vec) << 16), b1b = 0.5f * __uint_as_float(lds16(vec + 16) << 16);
    uint32_t wac[16], wd[16], wbc[16];
    {
      const int mi = lane >> 3, rr = lane & 7;
      const uint32_t a0 = sb + (8 * (mi >> 1) + rr) * 128 + (((2 * w + (mi & 1)) ^ rr) << 4);
#pragma unroll
      for (int ks = 0; ks < 4; ks++) {
        uint32_t A[4], Bm[4], C[4], Dm[4];
        ldsm_x4_t(a0 + ks * 2048 + w1_at(0), A[0], A[1], A[2], A[3]);
        ldsm_x4_t(a0 + ks * 2048 + w1_at(1), Bm[0], Bm[1], Bm[2], Bm[3]);
        ldsm_x4_t(a0 + ks * 2048 + w1_at(2), C[0], C[1], C[2], C[3]);
        ldsm_x4_t(a0 + ks * 2048 + w1_at(3), Dm[0], Dm[1], Dm[2], Dm[3]);
#pragma unroll
        for (int e = 0; e < 4; e++) {
          wac[4 * ks + e] = hfma2_bf16(A[e], half2, hfma2_bf16(C[e], half2, nzero2));
          wbc[4 * ks + e] = hfma2_bf16(Bm[e], half2, hfma2_bf16(C[e], nhalf2, nzero2));
          wd[4 * ks + e] = hfma2_bf16(Dm[e], half2, nzero2);
        }
      }
    }
    asm volatile("fence.proxy.async.shared::cta;" ::: "memory");
    asm volatile("bar.sync 5, %0;" :: "n"(NCW * 128) : "memory");

    const uint32_t ln = __shfl_sync(0xffffffffu, lane, lane);
    const uint32_t meta = __shfl_sync(0xffffffffu, 0x88dddd88u + (grid >> 20), lane);
    const uint32_t zr = grid >> 20;
    const uint32_t sel = keep<K_SEL>(((ring + R_SEL) & 0x3FFFF) >> 4);
    const uint32_t rat = __shfl_sync(0xffffffffu, w * 256 + sums_at(lane, 1024), lane);
    const uint32_t hi1c = DESC_ROWS + zr, hi2c = DESC_HALVES + zr;
    const uint32_t toff = __shfl_sync(0xffffffffu, (lane & 24) << 1, lane);
    const uint32_t ost = __shfl_sync(0xffffffffu, w * 1024 + (lane ^ ((lane >> 3) & 1)) * 16, lane);
    if (active) {
      uint32_t t[8];
      auto load_t = [&](uint32_t ta) {
        ldsm_x4(ta + toff, t[0], t[1], t[2], t[3]);
        ldsm_x4(ta + toff + 64, t[4], t[5], t[6], t[7]);
      };
      load_t(ring + R_TGT0);
      STAMP(1);
      uint32_t hdr = keep<1>(ring), raw, cur = hdr + (R_SPARE - S_EMPTY);
      auto next_header = [&]() {
        uint32_t x;
        asm volatile("{\n.reg .pred p;\n.reg .u32 n;\n.reg .s32 y;\n"
                     "ld.shared.u32 %0, [%1];\nxor.b32 y, %0, %2;\nsetp.ge.s32 p, y, 0;\n@p bra.uni FRESH;\n"
                     "and.b32 n, %2, %3;\nsetp.ne.u32 p, n, 0;\n@p bra.uni FRESH;\n"
                     "AGAIN:\nadd.u32 n, n, 1;\nsetp.gt.u32 p, n, 0x1000000;\n@p trap;\nnanosleep.u32 32;\n"
                     "ld.shared.u32 %0, [%1];\nxor.b32 y, %0, %2;\nsetp.lt.s32 p, y, 0;\n@p bra.uni AGAIN;\n"
                     "FRESH:\n}\n" : "=&r"(x) : "r"((hdr & H_NEXT) + S_HDR), "r"(hdr << 1), "n"(H_FINAL << 1) : "memory");
        raw = __shfl_sync(0xffffffffu, x, 0);
      };
      next_header();
      while (true) {
        __syncwarp();
        if (ln == 0) mbar_arrive(cur + S_EMPTY);
        cur = hdr & H_NEXT;
        hdr = raw;
        uint32_t we[16], bq[4];
        {
          float c[4][4];
          asm volatile("mma.sync.aligned.m16n8k16.row.col.f32.bf16.bf16.f32 {%0,%1,%2,%3}, {%4,%5,%6,%7}, {%8,%9}, {%10,%11,%12,%13};"
                       : "=f"(c[0][0]), "=f"(c[0][1]), "=f"(c[0][2]), "=f"(c[0][3])
                       : "r"(wbc[0]), "r"(wbc[1]), "r"(wbc[2]), "r"(wbc[3]), "r"(t[0]), "r"(t[1]), "f"(b1a), "f"(w2a), "f"(b1b), "f"(w2b));
#pragma unroll
          for (int i = 1; i < 4; i++) hmma<true>(c[i], wbc + 4 * i, t[2 * i], t[2 * i + 1]);
#pragma unroll
          for (int i = 0; i < 16; i++) we[i] = hfma2_bf16(t[i >> 1], wd[i], wac[i]);
#pragma unroll
          for (int i = 0; i < 4; i++) bq[i] = pack_bf16(c[i & 2][2 * (i & 1)], c[(i & 2) + 1][2 * (i & 1)]);
        }
        auto log_end = [&]() {
          LOGT(1);
        };
        auto chunk = [&](auto groups) {
          constexpr int N8 = decltype(groups)::value, KE = (N8 + 1) / 2, KA = KE - (N8 == 12 ? KL12 : KL);
          float d[4 * N8], o[16];
          uint32_t a[4 * KE];
          auto scores = [&](int i0, int i1) {
#pragma unroll
            for (int i = i0; i < i1; i++) {
              uint32_t p = i < N8 ? mix(d, i, w2a, w2b, c32) : 0;
              if (N8 == 16) {
                uint32_t m = 0x3f803f80u;
                asm volatile("{\n.reg .pred p;\nsetp.ne.u32 p, %1, 0;\n@p ld.shared.u32 %0, [%2];\n}\n"
                             : "+r"(m) : "r"(hdr & H_GENERAL), "r"(cur + S_MASK + i * 16 + (ln & 3) * 4) : "memory");
                p = hfma2_bf16(p, m, 0x80008000u);
              }
              a[2 * i] = a[2 * i + 1] = p;
            }
          };
          auto behind = [&](int i, int j) {
            asm volatile("{\n.reg .pred p;\nsetp.ne.u32 p, %2, 0;\n@p st.shared.u32 [%0], %1;\n}\n" :: "r"(a[2 * i]), "r"(a[2 * j]), "r"(zr) : "memory");
          };
          auto pin = [&](int k) {
            asm volatile("{\n.reg .pred p;\nsetp.ne.u32 p, %4, 0;\n@p st.shared.v4.u32 [%4], {%0,%1,%2,%3};\n}\n"
                         :: "r"(a[4 * k]), "r"(a[4 * k + 1]), "r"(a[4 * k + 2]), "r"(a[4 * k + 3]), "r"(zr) : "memory");
          };
          const uint32_t lo = cur >> 4, lo1 = lo + K_LO * 0x10000, lo2 = lo + K_LO2 * 0x10000;
          const uint32_t hi1 = K_HI1 == 0 ? hi1c : K_HI1 == 1 ? DESC_ROWS + (cur >> 24) : DESC_ROWS + (lo >> 19);
          const uint32_t hi2 = K_HI2 == 0 ? hi2c : K_HI2 == 1 ? DESC_HALVES + (cur >> 24) : K_HI2 == 2 ? hi1 + (DESC_HALVES - DESC_ROWS) : DESC_HALVES + (lo >> 18);
          auto g2 = [&](int k0, int k1) {
            mma_fence();
#pragma unroll
            for (int k = k0; k < k1; k++)
              if (k == 0) g2_first(o, a, lo2, meta, hi2); else g2_more(o, a + 4 * k, lo2 + 128 * k, meta, hi2);
            mma_commit();
          };
          mma_fence();
          g1_bias<NA>(d, bq, sel);
          g1_bias<N8 - NA>(d + 4 * NA, bq, sel);
          mma_commit();
          mbar_wait(cur + S_FULL, hdr >> 31);
          LOGT(0);
          mma_fence();
#pragma unroll
          for (int k = 0; k < 4; k++) g1_step<NA>(d, we + 4 * k, lo1 + 2 * k, hi1);
          mma_commit();
#pragma unroll
          for (int k = 0; k < 4; k++) g1_step<N8 - NA>(d + 4 * NA, we + 4 * k, lo1 + 64 * NA + 2 * k, hi1);
          mma_commit();
          mma_wait<1>(d, Int<NA>());
          tanh_some(d, 0, 4 * NA);
          scores(0, XP);
          if (XP == 4) { pin(0); pin(1); } else { behind(0, 1); if (XP > 2) behind(2, XP - 1); }
          mma_wait<0>(d + 4 * NA, Int<N8 - NA>());
          tanh_some(d, 4 * NA, 8 * KA);
          scores(XP, 2 * KA);
          g2(0, KA);
          tanh_some(d, 8 * KA, 4 * N8);
          scores(2 * KA, 2 * KE);
          g2(KA, KE);
          load_t(cur + S_TGT);
          next_header();
          mma_wait<0>(o, Int<4>());
#pragma unroll
          for (int e = 0; e < 2; e++)
            stsm_x4_t(cur + S_OUT + e * 512 + ost, pack_bf16(o[2 * e], o[2 * e + 1]), pack_bf16(o[2 * e + 4], o[2 * e + 5]),
                      pack_bf16(o[2 * e + 8], o[2 * e + 9]), pack_bf16(o[2 * e + 12], o[2 * e + 13]));
          log_end();
        };
        if (hdr & H_13) { chunk(Int<13>()); if (hdr & (H_FINAL | H_12)) break; }
        else if (hdr & H_12) { chunk(Int<12>()); if (hdr & (H_FINAL | H_14)) break; }
        else if (hdr & H_14) { chunk(Int<14>()); if (hdr & (H_FINAL | H_GENERAL)) break; }
        else { chunk(Int<16>()); if (hdr & H_FINAL) break; }
      }
      asm volatile("bar.sync %0, 128;" :: "r"(2 + wg) : "memory");
      const uint32_t ra = cur + rat;
      uint32_t* dst = reinterpret_cast<uint32_t*>(out) + (lds32(cur + S_ROW + 4 - (hdr >> 31) * 4) * 32 + 8 * w + (ln >> 2));
      uint32_t u[8];
      ldsm_x4(ra, u[0], u[1], u[2], u[3]);
      ldsm_x4(ra + 2048, u[4], u[5], u[6], u[7]);
      float c[4], e[4];
      hmma<true>(c, u, 0x3f803f80u, 0x3f803f80u);
      hmma<true>(e, u + 4, 0x3f803f80u, 0x3f803f80u);
      asm volatile("{\n.reg .pred p;\nsetp.lt.u32 p, %2, %3;\n@p st.global.u32 [%0], %1;\n}\n"
                   :: "l"(dst), "r"(pack_bf16(c[0] + e[0], c[2] + e[2])), "r"(ln & 3), "r"(hdr & H_SELF ? 1 : 0) : "memory");
      if (!(hdr & H_SELF) && ln == 0) mbar_arrive(cur + S_EMPTY);
    }
    STAMP(4);
  } else {
    const int pw = warp - NCW * 4;
    const uint32_t ring = sb + pw * RING_BYTES;
    asm volatile("setmaxnreg.dec.sync.aligned.u32 %0;" :: "n"(PROD_REGS));
    if (pw < NCW) {
      int b = pw * grid + blockIdx.x, bn = b + bstep;
      uint4 mw = load_mask(mask, min(b, B - 1), min(lane, 24));
      if (lane == 0) {
#pragma unroll
        for (int i = 0; i < NSLOT; i++) {
          mbar_init(ring + i * SLOT_BYTES + S_FULL, 34);
          mbar_init(ring + i * SLOT_BYTES + S_EMPTY, 4);
          mbar_arrive(ring + i * SLOT_BYTES + S_FULL);
          sts32(ring + i * SLOT_BYTES + S_HDR, 0x80000000u);
        }
        mbar_init(ring + R_SPARE, 5);
        sts32(ring + R_STOP, b < B && pw < ACT ? 0 : ring);
      }
      sts32(sb + R_PACE + lane * 4, 0);
      asm volatile("bar.arrive 1, %0;" :: "n"(NCW * 160) : "memory");
      asm volatile("bar.arrive 6, 128;" ::: "memory");
      if (pw >= ACT) return;
      const uint32_t list = ring + R_LIST;
      uint32_t lt;
      asm("mov.u32 %0, %%lanemask_lt;" : "=r"(lt));
      const uint32_t ln = __shfl_sync(0xffffffffu, lane, lane);
      const uint32_t r4 = (ln >> 3) * 4, c16 = (ln & 7) * 16, l25 = min(ln, 24u);
      const uint32_t pick = ln < 25 ? 0xeca8 : 0x9999;
      uint32_t dst[4];
#pragma unroll
      for (int i = 0; i < 4; i++) dst[i] = ring + (r4 + i) * 128 + (c16 ^ (((r4 + i) & 7) << 4));
      uint64_t pol;
      asm("createpolicy.fractional.L2::evict_first.b64 %0, 1.0;" : "=l"(pol));
      uint32_t sa = ring, phase = 1;
      const uint32_t wrap = (uint32_t)(max(B - NSTATIC * bstep, 0) + bstep - 1);
      auto next_slot = [&]() {
        const bool wrapped = sa == ring + (NSLOT - 1) * SLOT_BYTES;
        const int step = wrapped ? -(NSLOT - 1) * SLOT_BYTES : SLOT_BYTES;
        sa += step;
        phase ^= wrapped;
#pragma unroll
        for (int i = 0; i < 4; i++) dst[i] += step;
      };
      uint32_t claimer = ln;
      uint32_t drawn;
      auto draw = [&]() {
        drawn = B;
        asm volatile("{\n.reg .pred p;\nsetp.eq.u32 p, %3, 0;\n@p atom.global.inc.u32 %0, [%1], %2;\n}\n"
                     : "+r"(drawn) : "l"(counter), "r"(wrap), "r"(claimer) : "memory");
      };
      if (b >= B) draw();
      while (b < B) {
        const uint32_t e0 = nonzero_as_one(mw.x), e1 = nonzero_as_one(mw.y);
        const uint32_t e2 = nonzero_as_one(mw.z), e3 = nonzero_as_one(mw.w);
        const uint32_t nonbin = (e0 ^ mw.x) | (e1 ^ mw.y) | (e2 ^ mw.z) | (e3 ^ mw.w);
        const uint32_t sA = prmt(e0, e1, pick), sB = prmt(e2, e3, pick);
        const uint32_t pA = (sA & 0x01010101u) * 0x01010101u;
        const uint32_t pB = ((sB & 0x01010101u) + (pA >> 24)) * 0x01010101u;
        uint32_t pos = 0;
        int n = 0;
#pragma unroll
        for (int k = 0; k < 4; k++) {
          const uint32_t bal = ballot_bit(pB, 0x01000000u << k);
          pos += __popc(bal & lt) << k;
          n += __popc(bal) << k;
        }
        const uint32_t general = __any_sync(0xffffffffu, nonbin != 0);
        const uint32_t aA = (pA + pos * 0x01010101u) | ~sA, aB = (pB + pos * 0x01010101u) | ~sB;
#pragma unroll
        for (int i = 0; i < 8; i++) sts8(list - 1 + prmt(i < 4 ? aA : aB, 0, 0x4440 + (i & 3)), 8 * ln + i);
        __syncwarp();

        const uint64_t src = reinterpret_cast<uint64_t>(hist) + (uint64_t)b * (kL * kD * 2);
        const bool no_carry = (uint32_t)src <= 0xffffffffu - kL * kD * 2;
        auto begin_fill = [&](uint32_t h, uint32_t part, int nc, int bt, auto extra) {
          LOGT(0);
          int pace_now = pace;
          mbar_wait(sa + S_EMPTY, phase);
          if (bn >= tight_from) {
            if (bt >= B) {
              h |= H_FINAL;
              if (!part) { h |= H_SELF; sts32(ring + R_STOP, sa + (phase ^ 1)); }
              asm volatile("cp.async.wait_all;" ::: "memory");
            }
            const bool wrapped = sa == ring + (NSLOT - 1) * SLOT_BYTES;
            if (bn < B - OPEN_FROM) mbar_wait((wrapped ? ring : sa + SLOT_BYTES) + S_EMPTY, phase ^ wrapped);
            else pace_now = pace + END_PACE;
          }
          extra();
          {
            const bool wrapped = sa == ring + (NSLOT - 1) * SLOT_BYTES;
            sts32(sa + S_HDR, (h | (wrapped ? ring + 0x40000000u : sa + SLOT_BYTES)) ^ ((phase - 1) & 0xc0000000u));
          }
          sts32(sa + S_ROW + phase * 4, b | part);
          asm volatile("{\n.reg .pred p;\nsetp.eq.u32 p, %1, 0;\n@p mbarrier.arrive.shared::cta.b64 _, [%0];\n}\n"
                       :: "r"(sa + S_FULL), "r"(ln) : "memory");
          asm volatile("{\n.reg .u32 f, c;\n.reg .s32 d;\n.reg .pred p;\n"
                       "mov.u32 c, %%globaltimer_lo;\n"
                       "red.shared.max.u32 [%0], c;\n"
                       "atom.shared.add.u32 f, [%0], %1;\n"
                       "shfl.sync.idx.b32 f, f, 0, 31, 0xffffffff;\n"
                       "SPIN:\n"
                       "mov.u32 c, %%globaltimer_lo;\n"
                       "sub.s32 d, c, f;\n"
                       "setp.gt.u32 p, d, %2;\n"
                       "@p bra.uni SPIN;\n}\n" :: "r"(sb + R_PACE + ln * 4), "r"(nc * pace_now >> 4), "r"(~(pace * (CHUNK / 4))) : "memory");
          if (!(part & ROW_REST)) {
            mw = load_mask(mask, min(bn, B - 1), l25);
            draw();
          }
          LOGT(1);
          asm volatile("cp.async.ca.shared.global [%0], [%1], 4;"
                       :: "r"(sa + S_TGT + ln * 4), "l"(reinterpret_cast<const uint32_t*>(target) + ((uint32_t)min(bt, B - 1) * 32u + ln)) : "memory");
        };
        auto end_fill = [&](int nc) {
          cp_async_arrive_noinc(sa + S_FULL);
          next_slot();
          LOGT(2);
        };
        if (__builtin_expect(no_carry && !general, 1)) {
          int nc = n <= CHUNK ? n : n <= 160 ? 64 : 96;
          uint32_t la = list + r4, part = n <= CHUNK ? 0 : ROW_MORE;
#pragma unroll 1
          while (true) {
            uint32_t idx[7];
#pragma unroll
            for (int t = 0; t < 7; t++) idx[t] = lds32(la + t * 16);
            begin_fill(size_flag(nc), part, nc, part == ROW_MORE ? b : bn, [](){});
            const int left = nc - r4;
            const uint32_t base = (uint32_t)src + c16;
            uint64_t a[4];
            a[0] = a[1] = a[2] = a[3] = (uint64_t)((uint32_t)(src >> 32) + (ln >> 5)) << 32;
            if (__builtin_expect(nc >= 64, 1)) {
              cp_group<0>(dst, a, idx[0], base, pol);
              cp_group<1>(dst, a, idx[1], base, pol);
              cp_group<2>(dst, a, idx[2], base, pol);
              cp_group<3>(dst, a, idx[3], base, pol);
              cp_group_z<4>(dst, a, idx[4], base, left, pol);
              cp_group_z<5>(dst, a, idx[5], base, left, pol);
              if (nc > 96) {
                cp_group_z<6>(dst, a, idx[6], base, left, pol);
                if (nc > 112) cp_group_z<7>(dst, a, lds32(la + 112), base, left, pol);
              }
            } else {
              cp_group_z<0>(dst, a, idx[0], base, left, pol);
              cp_group_z<1>(dst, a, idx[1], base, left, pol);
              cp_group_z<2>(dst, a, idx[2], base, left, pol);
              cp_group_z<3>(dst, a, idx[3], base, left, pol);
              cp_group_z<4>(dst, a, 0, base, left, pol);
              cp_group_z<5>(dst, a, 0, base, left, pol);
            }
            end_fill(nc);
            if (part != ROW_MORE) break;
            la += nc;
            nc = n - nc;
            part = ROW_REST;
          }
        } else {
          int r0 = 0;
#pragma unroll 1
          do {
            const int nc = min(n - r0, CHUNK);
            const bool more = r0 + CHUNK < n;
            begin_fill(general ? H_GENERAL : size_flag(nc), (more ? ROW_MORE : 0u) | (r0 ? ROW_REST : 0u), nc, more ? b : bn, [&]() {
#pragma unroll 1
              for (int z = ln; general && z < CHUNK; z += 32) {
                uint32_t v = 0;
                if (z < nc) {
                  uint32_t row;
                  asm volatile("ld.shared.u8 %0, [%1];" : "=r"(row) : "r"(list + r0 + z) : "memory");
                  v = __bfloat16_as_ushort(mask[(size_t)b * kL + row]);
                }
                sts16(sa + S_MASK + z * 2, v);
              }
              __syncwarp();
            });
#pragma unroll 1
            for (int z = r4 >> 2; z < CHUNK; z += 4) {
              uint32_t row;
              asm volatile("ld.shared.u8 %0, [%1];" : "=r"(row) : "r"(list + r0 + z) : "memory");
              asm volatile("cp.async.cg.shared.global [%0], [%1], 16, %2;"
                           :: "r"(sa + z * 128 + (c16 ^ ((z & 7) << 4))), "l"(src + c16 + (z < nc ? row : 0) * 128),
                              "r"(z < nc ? 16 : 0) : "memory");
            }
            end_fill(nc);
            r0 += CHUNK;
          } while (r0 < n);
        }
        b = bn;
        bn = __shfl_sync(0xffffffffu, drawn, 0) + NSTATIC * bstep;
        if (bn >= B) claimer = 1;
      }
      STAMP(3);
      if (lds32(ring + R_STOP) == 0) sts32(ring + R_STOP, sa + (phase ^ 1));
      asm volatile("cp.async.wait_all;" ::: "memory");
      STAMP(4);
    } else {
      uint32_t due = clock();
      int s0 = NSTATIC * bstep + (PF_EARLY * grid + blockIdx.x) * PF_ROWS;
      auto prefetch = [&]() {
        const int cnt = min(PF_ROWS, B - s0);
        if (lane == 0) {
          prefetch_l2(mask + (size_t)s0 * kL, cnt * kL * 2);
          prefetch_l2(target + (size_t)s0 * kD, cnt * kD * 2);
        }
        s0 += grid * PF_ROWS;
      };
#pragma unroll 1
      for (int j = PF_EARLY; j < PF_FAST && s0 < B; j++) {
        while ((int)(due - (uint32_t)clock()) > 0) {}
        prefetch();
        due += PF_CYCLES;
      }
      due += (PF_FAST - 1) * PF_SLOW - (PF_FAST - PF_EARLY) * PF_CYCLES + (blockIdx.x & 255) * (PF_SLOW / 256);
      asm volatile("bar.sync 6, 128;" ::: "memory");
      static_assert(NCW == 3 && NSLOT < 4, "");
      uint32_t at = sb, at1 = sb + RING_BYTES, at2 = sb + 2 * RING_BYTES;
      const uint32_t ln = __shfl_sync(0xffffffffu, lane, lane);
      const uint32_t rd = __shfl_sync(0xffffffffu, sums_at(lane, 256), lane);
      uint32_t one[4];
#pragma unroll
      for (int i = 0; i < 4; i++) one[i] = __shfl_sync(0xffffffffu, lane >> 3 == i ? 0x3f803f80u : 0u, lane);
      uint32_t* const dst = reinterpret_cast<uint32_t*>(out) + ((lane & 3) * 8 + (lane >> 2));
      uint32_t idle = 0;
#pragma unroll 1
      while (at | at1 | at2) {
        const uint32_t sa = at & ~7u;
        if (at == 0) {
        } else if (__any_sync(0xffffffffu, mbar_test(sa + S_EMPTY, at & 1))) {
          const uint32_t row = lds32(sa + S_ROW + 4 - (at & 1) * 4);
          uint32_t u[8][4];
#pragma unroll
          for (int i = 0; i < 8; i++) ldsm_x4(sa + rd + i * 512, u[i][0], u[i][1], u[i][2], u[i][3]);
          float c[CHAINS][4];
#pragma unroll
          for (int l = 0; l < PREADD; l++)
#pragma unroll
            for (int i = 0; i < 4 >> l; i++)
#pragma unroll
              for (int e = 0; e < 4; e++) u[i][e] = hfma2_bf16(u[i][e], 0x3f803f80u, u[i + (4 >> l)][e]);
#pragma unroll
          for (int i = 0; i < 8 >> PREADD; i++)
            if (i < CHAINS) hmma<true>(c[i], u[i], one[2 * i & 2], one[(2 * i & 2) + 1]); else hmma<false>(c[i % CHAINS], u[i], one[2 * i & 2], one[(2 * i & 2) + 1]);
          float e0 = c[0][0], e1 = c[0][2];
#pragma unroll
          for (int i = 1; i < CHAINS; i++) { e0 += c[i][0]; e1 += c[i][2]; }
          __syncwarp();
          if (ln == 0) mbar_arrive(sa + S_FULL);
          at += SLOT_BYTES + 2;
          if ((at & 6) == 2 * NSLOT) at = (at - RING_BYTES - 2 * NSLOT) ^ 1;
          if (__builtin_expect(row >= ROW_REST, 0)) {
            const uint32_t carry = (at & ~7u) - (at & 6) * (SLOT_BYTES / 2) + R_CARRY + ln * 8;
            if (row & ROW_REST) { e0 += __uint_as_float(lds32(carry)); e1 += __uint_as_float(lds32(carry + 4)); }
            sts32(carry, __float_as_uint(e0));
            sts32(carry + 4, __float_as_uint(e1));
          }
          if (row < ROW_MORE) dst[(size_t)(row & (ROW_REST - 1)) * 32] = pack_bf16(e0, e1);
          idle = 0;
        } else {
          if (lds32(sa - (at & 6) * (SLOT_BYTES / 2) + R_STOP) == (at & ~6u)) at = 0;
          if (++idle > 2) {
            if (idle > 0x4000000) __trap();
            if (s0 < B && (int)(due - (uint32_t)clock()) <= 0) { prefetch(); due += PF_SLOW; }
            __nanosleep(RED_SLEEP);
          }
        }
        const uint32_t t = at; at = at1; at1 = at2; at2 = t;
      }
    }
  }
}

}

extern "C" void kernel_launch(void* const* d_in, const int* in_sizes, int n_in, void* d_out, int out_size) {
  const __nv_bfloat16* target = (const __nv_bfloat16*)d_in[0];
  const __nv_bfloat16* hist = (const __nv_bfloat16*)d_in[1];
  const __nv_bfloat16* mask = (const __nv_bfloat16*)d_in[2];
  const __nv_bfloat16* w1 = (const __nv_bfloat16*)d_in[3];
  const __nv_bfloat16* b1 = (const __nv_bfloat16*)d_in[4];
  const __nv_bfloat16* w2 = (const __nv_bfloat16*)d_in[5];
  const __nv_bfloat16* b2 = (const __nv_bfloat16*)d_in[6];
  const int B = in_sizes[0] / din::kD;
  if (B <= 0) return;
  static int sms = 0, pace = 0;
  static unsigned int* counter = nullptr;
  if (sms == 0) {
    int dev = 0, khz = 0, bits = 0;
    cudaGetDevice(&dev);
    cudaDeviceGetAttribute(&sms, cudaDevAttrMultiProcessorCount, dev);
    cudaDeviceGetAttribute(&khz, cudaDevAttrMemoryClockRate, dev);
    cudaDeviceGetAttribute(&bits, cudaDevAttrGlobalMemoryBusWidth, dev);
    if (khz > 0 && bits > 0) pace = (int)(16.0 * 128.0 * sms / (khz * 1e-6 * 2.0 * bits / 8.0));
    if (pace > 256) pace = 0;
    cudaGetSymbolAddress((void**)&counter, din::g_next);
    cudaFuncSetAttribute(din::din_kernel, cudaFuncAttributeMaxDynamicSharedMemorySize, din::SMEM_BYTES);
  }
  const long long early = (long long)(din::NSTATIC * NCW + PF_EARLY * PF_ROWS) * sms, line = 128LL * sms;
  long long pf_mask = (early * din::kL * 2 + line - 1) / line, pf_tgt = early * din::kD * 2 / line;
  if (pf_mask > (long long)B * din::kL * 2 / line) pf_mask = (long long)B * din::kL * 2 / line;
  if (pf_tgt > (long long)B * din::kD * 2 / line) pf_tgt = (long long)B * din::kD * 2 / line;
  din::din_kernel<<<sms, din::NTHREADS, din::SMEM_BYTES>>>(mask, target, B, sms, (uint32_t)pf_mask * 128, (uint32_t)pf_tgt * 128,
                                                          w1, hist, b1, w2, b2, (__nv_bfloat16*)d_out, counter, pace,
                                                          B - (TIGHT_ROUNDS > 0 ? TIGHT_ROUNDS : 0) * NCW * sms);
}
```

```cpp
#include <cuda_runtime.h>
#include <cuda_bf16.h>
#include <stdint.h>

namespace din {

constexpr int kL = 200, kD = 64;
#define NCW 3
#define NSLOT 3
constexpr int CHUNK = 128;
constexpr int NTHREADS = NCW * 128 + 128;
#define PREGS 56
#define CREGS 152
constexpr int PROD_REGS = PREGS, CONS_REGS = CREGS;
#define PF_ROWS 8
#define PF_FAST 10
#define PF_SLOW 2000
#define PF_CYCLES 280
#define RED_SLEEP 100
#define K_SEL 1
#define K_LO 1
#define K_LO2 2
#define K_HI1 2
#define K_HI2 2
#define K_CH 0
#define K_NX 0
#define K_NU 0
#define K_TOP 1
#define KL 2
#define KL12 1
#define NA 4
#define D0 5
#define KC 4
#define TFIRST 0
#define ORDER 1
#define NPAIR 2
#define PCUT 0
#define RCUT 1
#define LPOS 0
#define PF_EARLY 3
#define SLOW_ROUNDS 5
#define SLOW_BY 13
constexpr int NSTATIC = 2;
constexpr int S_TGT = CHUNK * 128;
constexpr int S_HDR = S_TGT + 128;
constexpr int S_FULL = S_HDR + 8;
constexpr int S_EMPTY = S_HDR + 16;
constexpr int S_ROW = S_HDR + 24;
constexpr int S_MASK = S_TGT + 256;
constexpr int S_OUT = S_TGT + 1024;
constexpr int SLOT_BYTES = S_OUT + 4096;
constexpr int RING_BYTES_ = NSLOT * SLOT_BYTES;
constexpr int R_PACE = 2 * RING_BYTES_ + S_TGT + 768;
constexpr int R_SPARE = S_HDR + 32;
constexpr int R_STOP = S_HDR + 44;
constexpr int R_LIST = S_TGT + 512;
constexpr int R_VEC = S_TGT + 768;
constexpr int R_SEL = S_TGT + 896;
constexpr int R_CARRY = SLOT_BYTES + S_TGT + 512;
constexpr int R_TGT0 = (NSLOT - 1) * SLOT_BYTES + S_OUT;
constexpr int RING_BYTES = NSLOT * SLOT_BYTES;
constexpr int SCALES = NCW * RING_BYTES + 32768;
constexpr int SMEM_BYTES = SCALES + 512 + 1024;
__device__ constexpr int w1_at(int i) { return NCW * RING_BYTES + i * 8192; }
#define LOGT(slot)
static_assert(SMEM_BYTES <= 232448, "shared memory");
constexpr uint32_t H_12 = 0x1f, H_13 = 0x20, H_14 = 0x40;
constexpr uint32_t H_GENERAL = 1u << 18, H_FINAL = 1u << 19, H_SELF = 1u << 20, H_NEXT = 0x3fc3fc00;
__device__ __forceinline__ uint32_t size_flag(int rows) { return 1u << ((rows - 57) >> 3); }
constexpr uint32_t ROW_REST = 1u << 30, ROW_MORE = 1u << 31;

__device__ unsigned int g_next;

#define RSTAMP(i)
#define WSTAMP(i)
#define STAMP(k)

#define STR2(x) #x
#define STR(x) STR2(x)
template<int V> struct Int { static constexpr int value = V; };
template<int G> __device__ __forceinline__ void g1_bias(float* d, const uint32_t (&bq)[4], uint32_t loSel);
template<int G> __device__ __forceinline__ void g1_step(float* d, const uint32_t* a, uint32_t loH, uint32_t hiH);
template<> __device__ __forceinline__ void g1_bias<4>(float* d, const uint32_t (&bq)[4], uint32_t loSel) {
  asm volatile("{\n.reg .b64 db;\n.reg .b32 zr;\n"
    "mov.b32 zr, 0;\nmov.b64 db, {%20, zr};\n"
    "wgmma.mma_async.sync.aligned.m64n32k16.f32.bf16.bf16 {%0, %1, %2, %3, %4, %5, %6, %7, %8, %9, %10, %11, %12, %13, %14, %15}, {%16, %17, %18, %19}, db, 0, 1, 1, 0;\n}\n"
    : "=f"(d[0]), "=f"(d[1]), "=f"(d[2]), "=f"(d[3]), "=f"(d[4]), "=f"(d[5]), "=f"(d[6]), "=f"(d[7]), "=f"(d[8]), "=f"(d[9]), "=f"(d[10]), "=f"(d[11]), "=f"(d[12]), "=f"(d[13]), "=f"(d[14]), "=f"(d[15])
    : "r"(bq[0]), "r"(bq[1]), "r"(bq[2]), "r"(bq[3]), "r"(loSel)
    : "memory");
}
template<> __device__ __forceinline__ void g1_bias<8>(float* d, const uint32_t (&bq)[4], uint32_t loSel) {
  asm volatile("{\n.reg .b64 db;\n.reg .b32 zr;\n"
    "mov.b32 zr, 0;\nmov.b64 db, {%36, zr};\n"
    "wgmma.mma_async.sync.aligned.m64n64k16.f32.bf16.bf16 {%0, %1, %2, %3, %4, %5, %6, %7, %8, %9, %10, %11, %12, %13, %14, %15, %16, %17, %18, %19, %20, %21, %22, %23, %24, %25, %26, %27, %28, %29, %30, %31}, {%32, %33, %34, %35}, db, 0, 1, 1, 0;\n}\n"
    : "=f"(d[0]), "=f"(d[1]), "=f"(d[2]), "=f"(d[3]), "=f"(d[4]), "=f"(d[5]), "=f"(d[6]), "=f"(d[7]), "=f"(d[8]), "=f"(d[9]), "=f"(d[10]), "=f"(d[11]), "=f"(d[12]), "=f"(d[13]), "=f"(d[14]), "=f"(d[15]), "=f"(d[16]), "=f"(d[17]), "=f"(d[18]), "=f"(d[19]), "=f"(d[20]), "=f"(d[21]), "=f"(d[22]), "=f"(d[23]), "=f"(d[24]), "=f"(d[25]), "=f"(d[26]), "=f"(d[27]), "=f"(d[28]), "=f"(d[29]), "=f"(d[30]), "=f"(d[31])
    : "r"(bq[0]), "r"(bq[1]), "r"(bq[2]), "r"(bq[3]), "r"(loSel)
    : "memory");
}
template<> __device__ __forceinline__ void g1_bias<9>(float* d, const uint32_t (&bq)[4], uint32_t loSel) {
  asm volatile("{\n.reg .b64 db;\n.reg .b32 zr;\n"
    "mov.b32 zr, 0;\nmov.b64 db, {%40, zr};\n"
    "wgmma.mma_async.sync.aligned.m64n72k16.f32.bf16.bf16 {%0, %1, %2, %3, %4, %5, %6, %7, %8, %9, %10, %11, %12, %13, %14, %15, %16, %17, %18, %19, %20, %21, %22, %23, %24, %25, %26, %27, %28, %29, %30, %31, %32, %33, %34, %35}, {%36, %37, %38, %39}, db, 0, 1, 1, 0;\n}\n"
    : "=f"(d[0]), "=f"(d[1]), "=f"(d[2]), "=f"(d[3]), "=f"(d[4]), "=f"(d[5]), "=f"(d[6]), "=f"(d[7]), "=f"(d[8]), "=f"(d[9]), "=f"(d[10]), "=f"(d[11]), "=f"(d[12]), "=f"(d[13]), "=f"(d[14]), "=f"(d[15]), "=f"(d[16]), "=f"(d[17]), "=f"(d[18]), "=f"(d[19]), "=f"(d[20]), "=f"(d[21]), "=f"(d[22]), "=f"(d[23]), "=f"(d[24]), "=f"(d[25]), "=f"(d[26]), "=f"(d[27]), "=f"(d[28]), "=f"(d[29]), "=f"(d[30]), "=f"(d[31]), "=f"(d[32]), "=f"(d[33]), "=f"(d[34]), "=f"(d[35])
    : "r"(bq[0]), "r"(bq[1]), "r"(bq[2]), "r"(bq[3]), "r"(loSel)
    : "memory");
}
template<> __device__ __forceinline__ void g1_bias<10>(float* d, const uint32_t (&bq)[4], uint32_t loSel) {
  asm volatile("{\n.reg .b64 db;\n.reg .b32 zr;\n"
    "mov.b32 zr, 0;\nmov.b64 db, {%44, zr};\n"
    "wgmma.mma_async.sync.aligned.m64n80k16.f32.bf16.bf16 {%0, %1, %2, %3, %4, %5, %6, %7, %8, %9, %10, %11, %12, %13, %14, %15, %16, %17, %18, %19, %20, %21, %22, %23, %24, %25, %26, %27, %28, %29, %30, %31, %32, %33, %34, %35, %36, %37, %38, %39}, {%40, %41, %42, %43}, db, 0, 1, 1, 0;\n}\n"
    : "=f"(d[0]), "=f"(d[1]), "=f"(d[2]), "=f"(d[3]), "=f"(d[4]), "=f"(d[5]), "=f"(d[6]), "=f"(d[7]), "=f"(d[8]), "=f"(d[9]), "=f"(d[10]), "=f"(d[11]), "=f"(d[12]), "=f"(d[13]), "=f"(d[14]), "=f"(d[15]), "=f"(d[16]), "=f"(d[17]), "=f"(d[18]), "=f"(d[19]), "=f"(d[20]), "=f"(d[21]), "=f"(d[22]), "=f"(d[23]), "=f"(d[24]), "=f"(d[25]), "=f"(d[26]), "=f"(d[27]), "=f"(d[28]), "=f"(d[29]), "=f"(d[30]), "=f"(d[31]), "=f"(d[32]), "=f"(d[33]), "=f"(d[34]), "=f"(d[35]), "=f"(d[36]), "=f"(d[37]), "=f"(d[38]), "=f"(d[39])
    : "r"(bq[0]), "r"(bq[1]), "r"(bq[2]), "r"(bq[3]), "r"(loSel)
    : "memory");
}
template<> __device__ __forceinline__ void g1_bias<12>(float* d, const uint32_t (&bq)[4], uint32_t loSel) {
  asm volatile("{\n.reg .b64 db;\n.reg .b32 zr;\n"
    "mov.b32 zr, 0;\nmov.b64 db, {%52, zr};\n"
    "wgmma.mma_async.sync.aligned.m64n96k16.f32.bf16.bf16 {%0, %1, %2, %3, %4, %5, %6, %7, %8, %9, %10, %11, %12, %13, %14, %15, %16, %17, %18, %19, %20, %21, %22, %23, %24, %25, %26, %27, %28, %29, %30, %31, %32, %33, %34, %35, %36, %37, %38, %39, %40, %41, %42, %43, %44, %45, %46, %47}, {%48, %49, %50, %51}, db, 0, 1, 1, 0;\n}\n"
    : "=f"(d[0]), "=f"(d[1]), "=f"(d[2]), "=f"(d[3]), "=f"(d[4]), "=f"(d[5]), "=f"(d[6]), "=f"(d[7]), "=f"(d[8]), "=f"(d[9]), "=f"(d[10]), "=f"(d[11]), "=f"(d[12]), "=f"(d[13]), "=f"(d[14]), "=f"(d[15]), "=f"(d[16]), "=f"(d[17]), "=f"(d[18]), "=f"(d[19]), "=f"(d[20]), "=f"(d[21]), "=f"(d[22]), "=f"(d[23]), "=f"(d[24]), "=f"(d[25]), "=f"(d[26]), "=f"(d[27]), "=f"(d[28]), "=f"(d[29]), "=f"(d[30]), "=f"(d[31]), "=f"(d[32]), "=f"(d[33]), "=f"(d[34]), "=f"(d[35]), "=f"(d[36]), "=f"(d[37]), "=f"(d[38]), "=f"(d[39]), "=f"(d[40]), "=f"(d[41]), "=f"(d[42]), "=f"(d[43]), "=f"(d[44]), "=f"(d[45]), "=f"(d[46]), "=f"(d[47])
    : "r"(bq[0]), "r"(bq[1]), "r"(bq[2]), "r"(bq[3]), "r"(loSel)
    : "memory");
}
template<> __device__ __forceinline__ void g1_step<4>(float* d, const uint32_t* a, uint32_t loH, uint32_t hiH) {
  asm volatile("{\n.reg .b64 db;\nmov.b64 db, {%20, %21};\n"
    "wgmma.mma_async.sync.aligned.m64n32k16.f32.bf16.bf16 {%0, %1, %2, %3, %4, %5, %6, %7, %8, %9, %10, %11, %12, %13, %14, %15}, {%16, %17, %18, %19}, db, 1, 1, 1, 0;\n}\n"
    : "+f"(d[0]), "+f"(d[1]), "+f"(d[2]), "+f"(d[3]), "+f"(d[4]), "+f"(d[5]), "+f"(d[6]), "+f"(d[7]), "+f"(d[8]), "+f"(d[9]), "+f"(d[10]), "+f"(d[11]), "+f"(d[12]), "+f"(d[13]), "+f"(d[14]), "+f"(d[15])
    : "r"(a[0]), "r"(a[1]), "r"(a[2]), "r"(a[3]), "r"(loH), "r"(hiH)
    : "memory");
}
template<> __device__ __forceinline__ void g1_step<8>(float* d, const uint32_t* a, uint32_t loH, uint32_t hiH) {
  asm volatile("{\n.reg .b64 db;\nmov.b64 db, {%36, %37};\n"
    "wgmma.mma_async.sync.aligned.m64n64k16.f32.bf16.bf16 {%0, %1, %2, %3, %4, %5, %6, %7, %8, %9, %10, %11, %12, %13, %14, %15, %16, %17, %18, %19, %20, %21, %22, %23, %24, %25, %26, %27, %28, %29, %30, %31}, {%32, %33, %34, %35}, db, 1, 1, 1, 0;\n}\n"
    : "+f"(d[0]), "+f"(d[1]), "+f"(d[2]), "+f"(d[3]), "+f"(d[4]), "+f"(d[5]), "+f"(d[6]), "+f"(d[7]), "+f"(d[8]), "+f"(d[9]), "+f"(d[10]), "+f"(d[11]), "+f"(d[12]), "+f"(d[13]), "+f"(d[14]), "+f"(d[15]), "+f"(d[16]), "+f"(d[17]), "+f"(d[18]), "+f"(d[19]), "+f"(d[20]), "+f"(d[21]), "+f"(d[22]), "+f"(d[23]), "+f"(d[24]), "+f"(d[25]), "+f"(d[26]), "+f"(d[27]), "+f"(d[28]), "+f"(d[29]), "+f"(d[30]), "+f"(d[31])
    : "r"(a[0]), "r"(a[1]), "r"(a[2]), "r"(a[3]), "r"(loH), "r"(hiH)
    : "memory");
}
template<> __device__ __forceinline__ void g1_step<9>(float* d, const uint32_t* a, uint32_t loH, uint32_t hiH) {
  asm volatile("{\n.reg .b64 db;\nmov.b64 db, {%40, %41};\n"
    "wgmma.mma_async.sync.aligned.m64n72k16.f32.bf16.bf16 {%0, %1, %2, %3, %4, %5, %6, %7, %8, %9, %10, %11, %12, %13, %14, %15, %16, %17, %18, %19, %20, %21, %22, %23, %24, %25, %26, %27, %28, %29, %30, %31, %32, %33, %34, %35}, {%36, %37, %38, %39}, db, 1, 1, 1, 0;\n}\n"
    : "+f"(d[0]), "+f"(d[1]), "+f"(d[2]), "+f"(d[3]), "+f"(d[4]), "+f"(d[5]), "+f"(d[6]), "+f"(d[7]), "+f"(d[8]), "+f"(d[9]), "+f"(d[10]), "+f"(d[11]), "+f"(d[12]), "+f"(d[13]), "+f"(d[14]), "+f"(d[15]), "+f"(d[16]), "+f"(d[17]), "+f"(d[18]), "+f"(d[19]), "+f"(d[20]), "+f"(d[21]), "+f"(d[22]), "+f"(d[23]), "+f"(d[24]), "+f"(d[25]), "+f"(d[26]), "+f"(d[27]), "+f"(d[28]), "+f"(d[29]), "+f"(d[30]), "+f"(d[31]), "+f"(d[32]), "+f"(d[33]), "+f"(d[34]), "+f"(d[35])
    : "r"(a[0]), "r"(a[1]), "r"(a[2]), "r"(a[3]), "r"(loH), "r"(hiH)
    : "memory");
}
template<> __device__ __forceinline__ void g1_step<10>(float* d, const uint32_t* a, uint32_t loH, uint32_t hiH) {
  asm volatile("{\n.reg .b64 db;\nmov.b64 db, {%44, %45};\n"
    "wgmma.mma_async.sync.aligned.m64n80k16.f32.bf16.bf16 {%0, %1, %2, %3, %4, %5, %6, %7, %8, %9, %10, %11, %12, %13, %14, %15, %16, %17, %18, %19, %20, %21, %22, %23, %24, %25, %26, %27, %28, %29, %30, %31, %32, %33, %34, %35, %36, %37, %38, %39}, {%40, %41, %42, %43}, db, 1, 1, 1, 0;\n}\n"
    : "+f"(d[0]), "+f"(d[1]), "+f"(d[2]), "+f"(d[3]), "+f"(d[4]), "+f"(d[5]), "+f"(d[6]), "+f"(d[7]), "+f"(d[8]), "+f"(d[9]), "+f"(d[10]), "+f"(d[11]), "+f"(d[12]), "+f"(d[13]), "+f"(d[14]), "+f"(d[15]), "+f"(d[16]), "+f"(d[17]), "+f"(d[18]), "+f"(d[19]), "+f"(d[20]), "+f"(d[21]), "+f"(d[22]), "+f"(d[23]), "+f"(d[24]), "+f"(d[25]), "+f"(d[26]), "+f"(d[27]), "+f"(d[28]), "+f"(d[29]), "+f"(d[30]), "+f"(d[31]), "+f"(d[32]), "+f"(d[33]), "+f"(d[34]), "+f"(d[35]), "+f"(d[36]), "+f"(d[37]), "+f"(d[38]), "+f"(d[39])
    : "r"(a[0]), "r"(a[1]), "r"(a[2]), "r"(a[3]), "r"(loH), "r"(hiH)
    : "memory");
}
template<> __device__ __forceinline__ void g1_step<12>(float* d, const uint32_t* a, uint32_t loH, uint32_t hiH) {
  asm volatile("{\n.reg .b64 db;\nmov.b64 db, {%52, %53};\n"
    "wgmma.mma_async.sync.aligned.m64n96k16.f32.bf16.bf16 {%0, %1, %2, %3, %4, %5, %6, %7, %8, %9, %10, %11, %12, %13, %14, %15, %16, %17, %18, %19, %20, %21, %22, %23, %24, %25, %26, %27, %28, %29, %30, %31, %32, %33, %34, %35, %36, %37, %38, %39, %40, %41, %42, %43, %44, %45, %46, %47}, {%48, %49, %50, %51}, db, 1, 1, 1, 0;\n}\n"
    : "+f"(d[0]), "+f"(d[1]), "+f"(d[2]), "+f"(d[3]), "+f"(d[4]), "+f"(d[5]), "+f"(d[6]), "+f"(d[7]), "+f"(d[8]), "+f"(d[9]), "+f"(d[10]), "+f"(d[11]), "+f"(d[12]), "+f"(d[13]), "+f"(d[14]), "+f"(d[15]), "+f"(d[16]), "+f"(d[17]), "+f"(d[18]), "+f"(d[19]), "+f"(d[20]), "+f"(d[21]), "+f"(d[22]), "+f"(d[23]), "+f"(d[24]), "+f"(d[25]), "+f"(d[26]), "+f"(d[27]), "+f"(d[28]), "+f"(d[29]), "+f"(d[30]), "+f"(d[31]), "+f"(d[32]), "+f"(d[33]), "+f"(d[34]), "+f"(d[35]), "+f"(d[36]), "+f"(d[37]), "+f"(d[38]), "+f"(d[39]), "+f"(d[40]), "+f"(d[41]), "+f"(d[42]), "+f"(d[43]), "+f"(d[44]), "+f"(d[45]), "+f"(d[46]), "+f"(d[47])
    : "r"(a[0]), "r"(a[1]), "r"(a[2]), "r"(a[3]), "r"(loH), "r"(hiH)
    : "memory");
}
template<int A, int G> __device__ __forceinline__ void g1_begin(float* d, const uint32_t (&bq)[4], uint32_t loSel, uint32_t bar, uint32_t parity);
template<> __device__ __forceinline__ void g1_begin<4, 12>(float* d, const uint32_t (&bq)[4], uint32_t loSel, uint32_t bar, uint32_t parity) {
  asm volatile("{\n.reg .b64 db;\n.reg .b32 n;\n.reg .pred p;\n"
    "mbarrier.test_wait.parity.shared::cta.b64 p, [%53], %54;\n"
    "mov.b32 n, 0;\nmov.b64 db, {%52, n};\nwgmma.fence.sync.aligned;\n"
    "wgmma.mma_async.sync.aligned.m64n32k16.f32.bf16.bf16 {%0, %1, %2, %3, %4, %5, %6, %7, %8, %9, %10, %11, %12, %13, %14, %15}, {%48, %49, %50, %51}, db, 0, 1, 1, 0;\n"
    "wgmma.mma_async.sync.aligned.m64n64k16.f32.bf16.bf16 {%16, %17, %18, %19, %20, %21, %22, %23, %24, %25, %26, %27, %28, %29, %30, %31, %32, %33, %34, %35, %36, %37, %38, %39, %40, %41, %42, %43, %44, %45, %46, %47}, {%48, %49, %50, %51}, db, 0, 1, 1, 0;\n"
    "wgmma.commit_group.sync.aligned;\n@p bra.uni THERE;\n"
    "AGAIN:\nmbarrier.try_wait.parity.shared::cta.b64 p, [%53], %54;\n@p bra.uni THERE;\n"
    "add.u32 n, n, 1;\nsetp.lt.u32 p, n, 0x1000000;\n@p bra.uni AGAIN;\ntrap;\nTHERE:\n}\n"
    : "=f"(d[0]), "=f"(d[1]), "=f"(d[2]), "=f"(d[3]), "=f"(d[4]), "=f"(d[5]), "=f"(d[6]), "=f"(d[7]), "=f"(d[8]), "=f"(d[9]), "=f"(d[10]), "=f"(d[11]), "=f"(d[12]), "=f"(d[13]), "=f"(d[14]), "=f"(d[15]), "=f"(d[16]), "=f"(d[17]), "=f"(d[18]), "=f"(d[19]), "=f"(d[20]), "=f"(d[21]), "=f"(d[22]), "=f"(d[23]), "=f"(d[24]), "=f"(d[25]), "=f"(d[26]), "=f"(d[27]), "=f"(d[28]), "=f"(d[29]), "=f"(d[30]), "=f"(d[31]), "=f"(d[32]), "=f"(d[33]), "=f"(d[34]), "=f"(d[35]), "=f"(d[36]), "=f"(d[37]), "=f"(d[38]), "=f"(d[39]), "=f"(d[40]), "=f"(d[41]), "=f"(d[42]), "=f"(d[43]), "=f"(d[44]), "=f"(d[45]), "=f"(d[46]), "=f"(d[47])
    : "r"(bq[0]), "r"(bq[1]), "r"(bq[2]), "r"(bq[3]), "r"(loSel), "r"(bar), "r"(parity)
    : "memory");
}
template<> __device__ __forceinline__ void g1_begin<4, 13>(float* d, const uint32_t (&bq)[4], uint32_t loSel, uint32_t bar, uint32_t parity) {
  asm volatile("{\n.reg .b64 db;\n.reg .b32 n;\n.reg .pred p;\n"
    "mbarrier.test_wait.parity.shared::cta.b64 p, [%57], %58;\n"
    "mov.b32 n, 0;\nmov.b64 db, {%56, n};\nwgmma.fence.sync.aligned;\n"
    "wgmma.mma_async.sync.aligned.m64n32k16.f32.bf16.bf16 {%0, %1, %2, %3, %4, %5, %6, %7, %8, %9, %10, %11, %12, %13, %14, %15}, {%52, %53, %54, %55}, db, 0, 1, 1, 0;\n"
    "wgmma.mma_async.sync.aligned.m64n72k16.f32.bf16.bf16 {%16, %17, %18, %19, %20, %21, %22, %23, %24, %25, %26, %27, %28, %29, %30, %31, %32, %33, %34, %35, %36, %37, %38, %39, %40, %41, %42, %43, %44, %45, %46, %47, %48, %49, %50, %51}, {%52, %53, %54, %55}, db, 0, 1, 1, 0;\n"
    "wgmma.commit_group.sync.aligned;\n@p bra.uni THERE;\n"
    "AGAIN:\nmbarrier.try_wait.parity.shared::cta.b64 p, [%57], %58;\n@p bra.uni THERE;\n"
    "add.u32 n, n, 1;\nsetp.lt.u32 p, n, 0x1000000;\n@p bra.uni AGAIN;\ntrap;\nTHERE:\n}\n"
    : "=f"(d[0]), "=f"(d[1]), "=f"(d[2]), "=f"(d[3]), "=f"(d[4]), "=f"(d[5]), "=f"(d[6]), "=f"(d[7]), "=f"(d[8]), "=f"(d[9]), "=f"(d[10]), "=f"(d[11]), "=f"(d[12]), "=f"(d[13]), "=f"(d[14]), "=f"(d[15]), "=f"(d[16]), "=f"(d[17]), "=f"(d[18]), "=f"(d[19]), "=f"(d[20]), "=f"(d[21]), "=f"(d[22]), "=f"(d[23]), "=f"(d[24]), "=f"(d[25]), "=f"(d[26]), "=f"(d[27]), "=f"(d[28]), "=f"(d[29]), "=f"(d[30]), "=f"(d[31]), "=f"(d[32]), "=f"(d[33]), "=f"(d[34]), "=f"(d[35]), "=f"(d[36]), "=f"(d[37]), "=f"(d[38]), "=f"(d[39]), "=f"(d[40]), "=f"(d[41]), "=f"(d[42]), "=f"(d[43]), "=f"(d[44]), "=f"(d[45]), "=f"(d[46]), "=f"(d[47]), "=f"(d[48]), "=f"(d[49]), "=f"(d[50]), "=f"(d[51])
    : "r"(bq[0]), "r"(bq[1]), "r"(bq[2]), "r"(bq[3]), "r"(loSel), "r"(bar), "r"(parity)
    : "memory");
}
template<> __device__ __forceinline__ void g1_begin<4, 14>(float* d, const uint32_t (&bq)[4], uint32_t loSel, uint32_t bar, uint32_t parity) {
  asm volatile("{\n.reg .b64 db;\n.reg .b32 n;\n.reg .pred p;\n"
    "mbarrier.test_wait.parity.shared::cta.b64 p, [%61], %62;\n"
    "mov.b32 n, 0;\nmov.b64 db, {%60, n};\nwgmma.fence.sync.aligned;\n"
    "wgmma.mma_async.sync.aligned.m64n32k16.f32.bf16.bf16 {%0, %1, %2, %3, %4, %5, %6, %7, %8, %9, %10, %11, %12, %13, %14, %15}, {%56, %57, %58, %59}, db, 0, 1, 1, 0;\n"
    "wgmma.mma_async.sync.aligned.m64n80k16.f32.bf16.bf16 {%16, %17, %18, %19, %20, %21, %22, %23, %24, %25, %26, %27, %28, %29, %30, %31, %32, %33, %34, %35, %36, %37, %38, %39, %40, %41, %42, %43, %44, %45, %46, %47, %48, %49, %50, %51, %52, %53, %54, %55}, {%56, %57, %58, %59}, db, 0, 1, 1, 0;\n"
    "wgmma.commit_group.sync.aligned;\n@p bra.uni THERE;\n"
    "AGAIN:\nmbarrier.try_wait.parity.shared::cta.b64 p, [%61], %62;\n@p bra.uni THERE;\n"
    "add.u32 n, n, 1;\nsetp.lt.u32 p, n, 0x1000000;\n@p bra.uni AGAIN;\ntrap;\nTHERE:\n}\n"
    : "=f"(d[0]), "=f"(d[1]), "=f"(d[2]), "=f"(d[3]), "=f"(d[4]), "=f"(d[5]), "=f"(d[6]), "=f"(d[7]), "=f"(d[8]), "=f"(d[9]), "=f"(d[10]), "=f"(d[11]), "=f"(d[12]), "=f"(d[13]), "=f"(d[14]), "=f"(d[15]), "=f"(d[16]), "=f"(d[17]), "=f"(d[18]), "=f"(d[19]), "=f"(d[20]), "=f"(d[21]), "=f"(d[22]), "=f"(d[23]), "=f"(d[24]), "=f"(d[25]), "=f"(d[26]), "=f"(d[27]), "=f"(d[28]), "=f"(d[29]), "=f"(d[30]), "=f"(d[31]), "=f"(d[32]), "=f"(d[33]), "=f"(d[34]), "=f"(d[35]), "=f"(d[36]), "=f"(d[37]), "=f"(d[38]), "=f"(d[39]), "=f"(d[40]), "=f"(d[41]), "=f"(d[42]), "=f"(d[43]), "=f"(d[44]), "=f"(d[45]), "=f"(d[46]), "=f"(d[47]), "=f"(d[48]), "=f"(d[49]), "=f"(d[50]), "=f"(d[51]), "=f"(d[52]), "=f"(d[53]), "=f"(d[54]), "=f"(d[55])
    : "r"(bq[0]), "r"(bq[1]), "r"(bq[2]), "r"(bq[3]), "r"(loSel), "r"(bar), "r"(parity)
    : "memory");
}
template<> __device__ __forceinline__ void g1_begin<4, 16>(float* d, const uint32_t (&bq)[4], uint32_t loSel, uint32_t bar, uint32_t parity) {
  asm volatile("{\n.reg .b64 db;\n.reg .b32 n;\n.reg .pred p;\n"
    "mbarrier.test_wait.parity.shared::cta.b64 p, [%69], %70;\n"
    "mov.b32 n, 0;\nmov.b64 db, {%68, n};\nwgmma.fence.sync.aligned;\n"
    "wgmma.mma_async.sync.aligned.m64n32k16.f32.bf16.bf16 {%0, %1, %2, %3, %4, %5, %6, %7, %8, %9, %10, %11, %12, %13, %14, %15}, {%64, %65, %66, %67}, db, 0, 1, 1, 0;\n"
    "wgmma.mma_async.sync.aligned.m64n96k16.f32.bf16.bf16 {%16, %17, %18, %19, %20, %21, %22, %23, %24, %25, %26, %27, %28, %29, %30, %31, %32, %33, %34, %35, %36, %37, %38, %39, %40, %41, %42, %43, %44, %45, %46, %47, %48, %49, %50, %51, %52, %53, %54, %55, %56, %57, %58, %59, %60, %61, %62, %63}, {%64, %65, %66, %67}, db, 0, 1, 1, 0;\n"
    "wgmma.commit_group.sync.aligned;\n@p bra.uni THERE;\n"
    "AGAIN:\nmbarrier.try_wait.parity.shared::cta.b64 p, [%69], %70;\n@p bra.uni THERE;\n"
    "add.u32 n, n, 1;\nsetp.lt.u32 p, n, 0x1000000;\n@p bra.uni AGAIN;\ntrap;\nTHERE:\n}\n"
    : "=f"(d[0]), "=f"(d[1]), "=f"(d[2]), "=f"(d[3]), "=f"(d[4]), "=f"(d[5]), "=f"(d[6]), "=f"(d[7]), "=f"(d[8]), "=f"(d[9]), "=f"(d[10]), "=f"(d[11]), "=f"(d[12]), "=f"(d[13]), "=f"(d[14]), "=f"(d[15]), "=f"(d[16]), "=f"(d[17]), "=f"(d[18]), "=f"(d[19]), "=f"(d[20]), "=f"(d[21]), "=f"(d[22]), "=f"(d[23]), "=f"(d[24]), "=f"(d[25]), "=f"(d[26]), "=f"(d[27]), "=f"(d[28]), "=f"(d[29]), "=f"(d[30]), "=f"(d[31]), "=f"(d[32]), "=f"(d[33]), "=f"(d[34]), "=f"(d[35]), "=f"(d[36]), "=f"(d[37]), "=f"(d[38]), "=f"(d[39]), "=f"(d[40]), "=f"(d[41]), "=f"(d[42]), "=f"(d[43]), "=f"(d[44]), "=f"(d[45]), "=f"(d[46]), "=f"(d[47]), "=f"(d[48]), "=f"(d[49]), "=f"(d[50]), "=f"(d[51]), "=f"(d[52]), "=f"(d[53]), "=f"(d[54]), "=f"(d[55]), "=f"(d[56]), "=f"(d[57]), "=f"(d[58]), "=f"(d[59]), "=f"(d[60]), "=f"(d[61]), "=f"(d[62]), "=f"(d[63])
    : "r"(bq[0]), "r"(bq[1]), "r"(bq[2]), "r"(bq[3]), "r"(loSel), "r"(bar), "r"(parity)
    : "memory");
}
template<> __device__ __forceinline__ void g1_begin<5, 12>(float* d, const uint32_t (&bq)[4], uint32_t loSel, uint32_t bar, uint32_t parity) {
  asm volatile("{\n.reg .b64 db;\n.reg .b32 n;\n.reg .pred p;\n"
    "mbarrier.test_wait.parity.shared::cta.b64 p, [%53], %54;\n"
    "mov.b32 n, 0;\nmov.b64 db, {%52, n};\nwgmma.fence.sync.aligned;\n"
    "wgmma.mma_async.sync.aligned.m64n40k16.f32.bf16.bf16 {%0, %1, %2, %3, %4, %5, %6, %7, %8, %9, %10, %11, %12, %13, %14, %15, %16, %17, %18, %19}, {%48, %49, %50, %51}, db, 0, 1, 1, 0;\n"
    "wgmma.mma_async.sync.aligned.m64n56k16.f32.bf16.bf16 {%20, %21, %22, %23, %24, %25, %26, %27, %28, %29, %30, %31, %32, %33, %34, %35, %36, %37, %38, %39, %40, %41, %42, %43, %44, %45, %46, %47}, {%48, %49, %50, %51}, db, 0, 1, 1, 0;\n"
    "wgmma.commit_group.sync.aligned;\n@p bra.uni THERE;\n"
    "AGAIN:\nmbarrier.try_wait.parity.shared::cta.b64 p, [%53], %54;\n@p bra.uni THERE;\n"
    "add.u32 n, n, 1;\nsetp.lt.u32 p, n, 0x1000000;\n@p bra.uni AGAIN;\ntrap;\nTHERE:\n}\n"
    : "=f"(d[0]), "=f"(d[1]), "=f"(d[2]), "=f"(d[3]), "=f"(d[4]), "=f"(d[5]), "=f"(d[6]), "=f"(d[7]), "=f"(d[8]), "=f"(d[9]), "=f"(d[10]), "=f"(d[11]), "=f"(d[12]), "=f"(d[13]), "=f"(d[14]), "=f"(d[15]), "=f"(d[16]), "=f"(d[17]), "=f"(d[18]), "=f"(d[19]), "=f"(d[20]), "=f"(d[21]), "=f"(d[22]), "=f"(d[23]), "=f"(d[24]), "=f"(d[25]), "=f"(d[26]), "=f"(d[27]), "=f"(d[28]), "=f"(d[29]), "=f"(d[30]), "=f"(d[31]), "=f"(d[32]), "=f"(d[33]), "=f"(d[34]), "=f"(d[35]), "=f"(d[36]), "=f"(d[37]), "=f"(d[38]), "=f"(d[39]), "=f"(d[40]), "=f"(d[41]), "=f"(d[42]), "=f"(d[43]), "=f"(d[44]), "=f"(d[45]), "=f"(d[46]), "=f"(d[47])
    : "r"(bq[0]), "r"(bq[1]), "r"(bq[2]), "r"(bq[3]), "r"(loSel), "r"(bar), "r"(parity)
    : "memory");
}
template<> __device__ __forceinline__ void g1_begin<5, 13>(float* d, const uint32_t (&bq)[4], uint32_t loSel, uint32_t bar, uint32_t parity) {
  asm volatile("{\n.reg .b64 db;\n.reg .b32 n;\n.reg .pred p;\n"
    "mbarrier.test_wait.parity.shared::cta.b64 p, [%57], %58;\n"
    "mov.b32 n, 0;\nmov.b64 db, {%56, n};\nwgmma.fence.sync.aligned;\n"
    "wgmma.mma_async.sync.aligned.m64n40k16.f32.bf16.bf16 {%0, %1, %2, %3, %4, %5, %6, %7, %8, %9, %10, %11, %12, %13, %14, %15, %16, %17, %18, %19}, {%52, %53, %54, %55}, db, 0, 1, 1, 0;\n"
    "wgmma.mma_async.sync.aligned.m64n64k16.f32.bf16.bf16 {%20, %21, %22, %23, %24, %25, %26, %27, %28, %29, %30, %31, %32, %33, %34, %35, %36, %37, %38, %39, %40, %41, %42, %43, %44, %45, %46, %47, %48, %49, %50, %51}, {%52, %53, %54, %55}, db, 0, 1, 1, 0;\n"
    "wgmma.commit_group.sync.aligned;\n@p bra.uni THERE;\n"
    "AGAIN:\nmbarrier.try_wait.parity.shared::cta.b64 p, [%57], %58;\n@p bra.uni THERE;\n"
    "add.u32 n, n, 1;\nsetp.lt.u32 p, n, 0x1000000;\n@p bra.uni AGAIN;\ntrap;\nTHERE:\n}\n"
    : "=f"(d[0]), "=f"(d[1]), "=f"(d[2]), "=f"(d[3]), "=f"(d[4]), "=f"(d[5]), "=f"(d[6]), "=f"(d[7]), "=f"(d[8]), "=f"(d[9]), "=f"(d[10]), "=f"(d[11]), "=f"(d[12]), "=f"(d[13]), "=f"(d[14]), "=f"(d[15]), "=f"(d[16]), "=f"(d[17]), "=f"(d[18]), "=f"(d[19]), "=f"(d[20]), "=f"(d[21]), "=f"(d[22]), "=f"(d[23]), "=f"(d[24]), "=f"(d[25]), "=f"(d[26]), "=f"(d[27]), "=f"(d[28]), "=f"(d[29]), "=f"(d[30]), "=f"(d[31]), "=f"(d[32]), "=f"(d[33]), "=f"(d[34]), "=f"(d[35]), "=f"(d[36]), "=f"(d[37]), "=f"(d[38]), "=f"(d[39]), "=f"(d[40]), "=f"(d[41]), "=f"(d[42]), "=f"(d[43]), "=f"(d[44]), "=f"(d[45]), "=f"(d[46]), "=f"(d[47]), "=f"(d[48]), "=f"(d[49]), "=f"(d[50]), "=f"(d[51])
    : "r"(bq[0]), "r"(bq[1]), "r"(bq[2]), "r"(bq[3]), "r"(loSel), "r"(bar), "r"(parity)
    : "memory");
}
template<> __device__ __forceinline__ void g1_begin<5, 14>(float* d, const uint32_t (&bq)[4], uint32_t loSel, uint32_t bar, uint32_t parity) {
  asm volatile("{\n.reg .b64 db;\n.reg .b32 n;\n.reg .pred p;\n"
    "mbarrier.test_wait.parity.shared::cta.b64 p, [%61], %62;\n"
    "mov.b32 n, 0;\nmov.b64 db, {%60, n};\nwgmma.fence.sync.aligned;\n"
    "wgmma.mma_async.sync.aligned.m64n40k16.f32.bf16.bf16 {%0, %1, %2, %3, %4, %5, %6, %7, %8, %9, %10, %11, %12, %13, %14, %15, %16, %17, %18, %19}, {%56, %57, %58, %59}, db, 0, 1, 1, 0;\n"
    "wgmma.mma_async.sync.aligned.m64n72k16.f32.bf16.bf16 {%20, %21, %22, %23, %24, %25, %26, %27, %28, %29, %30, %31, %32, %33, %34, %35, %36, %37, %38, %39, %40, %41, %42, %43, %44, %45, %46, %47, %48, %49, %50, %51, %52, %53, %54, %55}, {%56, %57, %58, %59}, db, 0, 1, 1, 0;\n"
    "wgmma.commit_group.sync.aligned;\n@p bra.uni THERE;\n"
    "AGAIN:\nmbarrier.try_wait.parity.shared::cta.b64 p, [%61], %62;\n@p bra.uni THERE;\n"
    "add.u32 n, n, 1;\nsetp.lt.u32 p, n, 0x1000000;\n@p bra.uni AGAIN;\ntrap;\nTHERE:\n}\n"
    : "=f"(d[0]), "=f"(d[1]), "=f"(d[2]), "=f"(d[3]), "=f"(d[4]), "=f"(d[5]), "=f"(d[6]), "=f"(d[7]), "=f"(d[8]), "=f"(d[9]), "=f"(d[10]), "=f"(d[11]), "=f"(d[12]), "=f"(d[13]), "=f"(d[14]), "=f"(d[15]), "=f"(d[16]), "=f"(d[17]), "=f"(d[18]), "=f"(d[19]), "=f"(d[20]), "=f"(d[21]), "=f"(d[22]), "=f"(d[23]), "=f"(d[24]), "=f"(d[25]), "=f"(d[26]), "=f"(d[27]), "=f"(d[28]), "=f"(d[29]), "=f"(d[30]), "=f"(d[31]), "=f"(d[32]), "=f"(d[33]), "=f"(d[34]), "=f"(d[35]), "=f"(d[36]), "=f"(d[37]), "=f"(d[38]), "=f"(d[39]), "=f"(d[40]), "=f"(d[41]), "=f"(d[42]), "=f"(d[43]), "=f"(d[44]), "=f"(d[45]), "=f"(d[46]), "=f"(d[47]), "=f"(d[48]), "=f"(d[49]), "=f"(d[50]), "=f"(d[51]), "=f"(d[52]), "=f"(d[53]), "=f"(d[54]), "=f"(d[55])
    : "r"(bq[0]), "r"(bq[1]), "r"(bq[2]), "r"(bq[3]), "r"(loSel), "r"(bar), "r"(parity)
    : "memory");
}
template<> __device__ __forceinline__ void g1_begin<5, 16>(float* d, const uint32_t (&bq)[4], uint32_t loSel, uint32_t bar, uint32_t parity) {
  asm volatile("{\n.reg .b64 db;\n.reg .b32 n;\n.reg .pred p;\n"
    "mbarrier.test_wait.parity.shared::cta.b64 p, [%69], %70;\n"
    "mov.b32 n, 0;\nmov.b64 db, {%68, n};\nwgmma.fence.sync.aligned;\n"
    "wgmma.mma_async.sync.aligned.m64n40k16.f32.bf16.bf16 {%0, %1, %2, %3, %4, %5, %6, %7, %8, %9, %10, %11, %12, %13, %14, %15, %16, %17, %18, %19}, {%64, %65, %66, %67}, db, 0, 1, 1, 0;\n"
    "wgmma.mma_async.sync.aligned.m64n88k16.f32.bf16.bf16 {%20, %21, %22, %23, %24, %25, %26, %27, %28, %29, %30, %31, %32, %33, %34, %35, %36, %37, %38, %39, %40, %41, %42, %43, %44, %45, %46, %47, %48, %49, %50, %51, %52, %53, %54, %55, %56, %57, %58, %59, %60, %61, %62, %63}, {%64, %65, %66, %67}, db, 0, 1, 1, 0;\n"
    "wgmma.commit_group.sync.aligned;\n@p bra.uni THERE;\n"
    "AGAIN:\nmbarrier.try_wait.parity.shared::cta.b64 p, [%69], %70;\n@p bra.uni THERE;\n"
    "add.u32 n, n, 1;\nsetp.lt.u32 p, n, 0x1000000;\n@p bra.uni AGAIN;\ntrap;\nTHERE:\n}\n"
    : "=f"(d[0]), "=f"(d[1]), "=f"(d[2]), "=f"(d[3]), "=f"(d[4]), "=f"(d[5]), "=f"(d[6]), "=f"(d[7]), "=f"(d[8]), "=f"(d[9]), "=f"(d[10]), "=f"(d[11]), "=f"(d[12]), "=f"(d[13]), "=f"(d[14]), "=f"(d[15]), "=f"(d[16]), "=f"(d[17]), "=f"(d[18]), "=f"(d[19]), "=f"(d[20]), "=f"(d[21]), "=f"(d[22]), "=f"(d[23]), "=f"(d[24]), "=f"(d[25]), "=f"(d[26]), "=f"(d[27]), "=f"(d[28]), "=f"(d[29]), "=f"(d[30]), "=f"(d[31]), "=f"(d[32]), "=f"(d[33]), "=f"(d[34]), "=f"(d[35]), "=f"(d[36]), "=f"(d[37]), "=f"(d[38]), "=f"(d[39]), "=f"(d[40]), "=f"(d[41]), "=f"(d[42]), "=f"(d[43]), "=f"(d[44]), "=f"(d[45]), "=f"(d[46]), "=f"(d[47]), "=f"(d[48]), "=f"(d[49]), "=f"(d[50]), "=f"(d[51]), "=f"(d[52]), "=f"(d[53]), "=f"(d[54]), "=f"(d[55]), "=f"(d[56]), "=f"(d[57]), "=f"(d[58]), "=f"(d[59]), "=f"(d[60]), "=f"(d[61]), "=f"(d[62]), "=f"(d[63])
    : "r"(bq[0]), "r"(bq[1]), "r"(bq[2]), "r"(bq[3]), "r"(loSel), "r"(bar), "r"(parity)
    : "memory");
}
__device__ __forceinline__ void g2_first(float (&o)[16], const uint32_t* a, uint32_t loH, uint32_t meta, uint32_t hiH) {
  asm volatile("{\n.reg .b64 db;\nmov.b64 db, {%20, %22};\n"
    "wgmma.mma_async.sp.sync.aligned.m64n32k32.f32.bf16.bf16 {%0, %1, %2, %3, %4, %5, %6, %7, %8, %9, %10, %11, %12, %13, %14, %15}, {%16, %17, %18, %19}, db, %21, 0, 0, 1, 1, 1;\n}\n"
    : "=f"(o[0]), "=f"(o[1]), "=f"(o[2]), "=f"(o[3]), "=f"(o[4]), "=f"(o[5]), "=f"(o[6]), "=f"(o[7]), "=f"(o[8]), "=f"(o[9]), "=f"(o[10]), "=f"(o[11]), "=f"(o[12]), "=f"(o[13]), "=f"(o[14]), "=f"(o[15])
    : "r"(a[0]), "r"(a[1]), "r"(a[2]), "r"(a[3]), "r"(loH), "r"(meta), "r"(hiH)
    : "memory");
}
__device__ __forceinline__ void g2_more(float (&o)[16], const uint32_t* a, uint32_t loH, uint32_t meta, uint32_t hiH) {
  asm volatile("{\n.reg .b64 db;\nmov.b64 db, {%20, %22};\n"
    "wgmma.mma_async.sp.sync.aligned.m64n32k32.f32.bf16.bf16 {%0, %1, %2, %3, %4, %5, %6, %7, %8, %9, %10, %11, %12, %13, %14, %15}, {%16, %17, %18, %19}, db, %21, 0, 1, 1, 1, 1;\n}\n"
    : "+f"(o[0]), "+f"(o[1]), "+f"(o[2]), "+f"(o[3]), "+f"(o[4]), "+f"(o[5]), "+f"(o[6]), "+f"(o[7]), "+f"(o[8]), "+f"(o[9]), "+f"(o[10]), "+f"(o[11]), "+f"(o[12]), "+f"(o[13]), "+f"(o[14]), "+f"(o[15])
    : "r"(a[0]), "r"(a[1]), "r"(a[2]), "r"(a[3]), "r"(loH), "r"(meta), "r"(hiH)
    : "memory");
}
template<int N> __device__ __forceinline__ void mma_wait(float* d, Int<4>) {
  asm volatile("wgmma.wait_group.sync.aligned %16;"
    : "+f"(d[0]), "+f"(d[1]), "+f"(d[2]), "+f"(d[3]), "+f"(d[4]), "+f"(d[5]), "+f"(d[6]), "+f"(d[7]), "+f"(d[8]), "+f"(d[9]), "+f"(d[10]), "+f"(d[11]), "+f"(d[12]), "+f"(d[13]), "+f"(d[14]), "+f"(d[15])
    : "n"(N) : "memory");
}
template<int N> __device__ __forceinline__ void mma_wait(float* d, Int<8>) {
  asm volatile("wgmma.wait_group.sync.aligned %32;"
    : "+f"(d[0]), "+f"(d[1]), "+f"(d[2]), "+f"(d[3]), "+f"(d[4]), "+f"(d[5]), "+f"(d[6]), "+f"(d[7]), "+f"(d[8]), "+f"(d[9]), "+f"(d[10]), "+f"(d[11]), "+f"(d[12]), "+f"(d[13]), "+f"(d[14]), "+f"(d[15]), "+f"(d[16]), "+f"(d[17]), "+f"(d[18]), "+f"(d[19]), "+f"(d[20]), "+f"(d[21]), "+f"(d[22]), "+f"(d[23]), "+f"(d[24]), "+f"(d[25]), "+f"(d[26]), "+f"(d[27]), "+f"(d[28]), "+f"(d[29]), "+f"(d[30]), "+f"(d[31])
    : "n"(N) : "memory");
}
template<int N> __device__ __forceinline__ void mma_wait(float* d, Int<9>) {
  asm volatile("wgmma.wait_group.sync.aligned %36;"
    : "+f"(d[0]), "+f"(d[1]), "+f"(d[2]), "+f"(d[3]), "+f"(d[4]), "+f"(d[5]), "+f"(d[6]), "+f"(d[7]), "+f"(d[8]), "+f"(d[9]), "+f"(d[10]), "+f"(d[11]), "+f"(d[12]), "+f"(d[13]), "+f"(d[14]), "+f"(d[15]), "+f"(d[16]), "+f"(d[17]), "+f"(d[18]), "+f"(d[19]), "+f"(d[20]), "+f"(d[21]), "+f"(d[22]), "+f"(d[23]), "+f"(d[24]), "+f"(d[25]), "+f"(d[26]), "+f"(d[27]), "+f"(d[28]), "+f"(d[29]), "+f"(d[30]), "+f"(d[31]), "+f"(d[32]), "+f"(d[33]), "+f"(d[34]), "+f"(d[35])
    : "n"(N) : "memory");
}
template<int N> __device__ __forceinline__ void mma_wait(float* d, Int<10>) {
  asm volatile("wgmma.wait_group.sync.aligned %40;"
    : "+f"(d[0]), "+f"(d[1]), "+f"(d[2]), "+f"(d[3]), "+f"(d[4]), "+f"(d[5]), "+f"(d[6]), "+f"(d[7]), "+f"(d[8]), "+f"(d[9]), "+f"(d[10]), "+f"(d[11]), "+f"(d[12]), "+f"(d[13]), "+f"(d[14]), "+f"(d[15]), "+f"(d[16]), "+f"(d[17]), "+f"(d[18]), "+f"(d[19]), "+f"(d[20]), "+f"(d[21]), "+f"(d[22]), "+f"(d[23]), "+f"(d[24]), "+f"(d[25]), "+f"(d[26]), "+f"(d[27]), "+f"(d[28]), "+f"(d[29]), "+f"(d[30]), "+f"(d[31]), "+f"(d[32]), "+f"(d[33]), "+f"(d[34]), "+f"(d[35]), "+f"(d[36]), "+f"(d[37]), "+f"(d[38]), "+f"(d[39])
    : "n"(N) : "memory");
}
template<int N> __device__ __forceinline__ void mma_wait(float* d, Int<12>) {
  asm volatile("wgmma.wait_group.sync.aligned %48;"
    : "+f"(d[0]), "+f"(d[1]), "+f"(d[2]), "+f"(d[3]), "+f"(d[4]), "+f"(d[5]), "+f"(d[6]), "+f"(d[7]), "+f"(d[8]), "+f"(d[9]), "+f"(d[10]), "+f"(d[11]), "+f"(d[12]), "+f"(d[13]), "+f"(d[14]), "+f"(d[15]), "+f"(d[16]), "+f"(d[17]), "+f"(d[18]), "+f"(d[19]), "+f"(d[20]), "+f"(d[21]), "+f"(d[22]), "+f"(d[23]), "+f"(d[24]), "+f"(d[25]), "+f"(d[26]), "+f"(d[27]), "+f"(d[28]), "+f"(d[29]), "+f"(d[30]), "+f"(d[31]), "+f"(d[32]), "+f"(d[33]), "+f"(d[34]), "+f"(d[35]), "+f"(d[36]), "+f"(d[37]), "+f"(d[38]), "+f"(d[39]), "+f"(d[40]), "+f"(d[41]), "+f"(d[42]), "+f"(d[43]), "+f"(d[44]), "+f"(d[45]), "+f"(d[46]), "+f"(d[47])
    : "n"(N) : "memory");
}

__device__ __forceinline__ uint32_t smem_u32(const void* p) { return (uint32_t)__cvta_generic_to_shared(p); }

__device__ __forceinline__ void mbar_init(uint32_t bar, uint32_t cnt) {
  asm volatile("mbarrier.init.shared::cta.b64 [%0], %1;" :: "r"(bar), "r"(cnt) : "memory");
}
__device__ __forceinline__ void mbar_arrive(uint32_t bar) {
  asm volatile("mbarrier.arrive.shared::cta.b64 _, [%0];" :: "r"(bar) : "memory");
}
__device__ __forceinline__ void mbar_wait(uint32_t bar, uint32_t parity) {
  asm volatile("{\n.reg .pred p;\n.reg .u32 n;\n"
               "mov.u32 n, 0;\n"
               "WAIT_LOOP:\n"
               "mbarrier.try_wait.parity.shared::cta.b64 p, [%0], %1;\n"
               "@p bra.uni WAIT_DONE;\n"
               "add.u32 n, n, 1;\n"
               "setp.lt.u32 p, n, 0x1000000;\n"
               "@p bra.uni WAIT_LOOP;\n"
               "trap;\n"
               "WAIT_DONE:\n}\n"
               :: "r"(bar), "r"(parity) : "memory");
}
__device__ __forceinline__ uint32_t mbar_test(uint32_t bar, uint32_t parity) {
  uint32_t ok;
  asm volatile("{\n.reg .pred p;\nmbarrier.test_wait.parity.shared::cta.b64 p, [%1], %2;\nselp.u32 %0, 1, 0, p;\n}\n"
               : "=r"(ok) : "r"(bar), "r"(parity) : "memory");
  return ok;
}
__device__ __forceinline__ void cp_async16(uint32_t dst, const void* src) {
  asm volatile("cp.async.cg.shared.global [%0], [%1], 16;" :: "r"(dst), "l"(src) : "memory");
}
template<int T, int I, bool Z>
__device__ __forceinline__ void cp_row(uint32_t dst, uint64_t& a, uint32_t rows4, uint32_t base, int left, uint64_t pol) {
#define DIN_ADDR "mov.b64 {x, y}, %0;\ndp4a.u32.u32 x, %2, %8, %5;\nmov.b64 %0, {x, y};\n"
  if (Z)
    asm volatile("{\n.reg .u32 x, y;\n.reg .pred p, q;\n" DIN_ADDR "setp.le.s32 p, %6, %7;\n"
                 "cp.async.cg.shared.global.L2::cache_hint [%1 + %4], [%0], 16, p, %3;\n}\n"
                 : "+l"(a) : "r"(dst), "r"(rows4), "l"(pol), "n"(T * 2048), "r"(base), "r"(left), "n"(T * 16 + I), "n"(0x80u << 8 * I) : "memory");
  else
    asm volatile("{\n.reg .u32 x, y;\n.reg .pred q;\n" DIN_ADDR
                 "cp.async.cg.shared.global.L2::cache_hint [%1 + %4], [%0], 16, %3;\n}\n"
                 : "+l"(a) : "r"(dst), "r"(rows4), "l"(pol), "n"(T * 2048), "r"(base), "r"(left), "n"(T * 16 + I), "n"(0x80u << 8 * I) : "memory");
}
template<int T, bool Z>
__device__ __forceinline__ void cp_group(const uint32_t (&dst)[4], uint64_t (&a)[NPAIR], uint32_t rows4, uint32_t base, int left, uint64_t pol, uint32_t& any) {
  auto cut = [&](int i) {
    if (PCUT && i % (PCUT ? PCUT : 1) == 0)
      asm volatile("{\n.reg .pred p;\nsetp.lt.s32 p, %1, 0;\n@p mov.u32 %0, %%clock;\n}\n" : "+r"(any) : "r"(left) : "memory");
  };
  cp_row<T, 0, Z>(dst[0], a[(4 * T) % NPAIR], rows4, base, left, pol);
  cut(1);
  cp_row<T, 1, Z>(dst[1], a[(4 * T + 1) % NPAIR], rows4, base, left, pol);
  cut(2);
  cp_row<T, 2, Z>(dst[2], a[(4 * T + 2) % NPAIR], rows4, base, left, pol);
  cut(3);
  cp_row<T, 3, Z>(dst[3], a[(4 * T + 3) % NPAIR], rows4, base, left, pol);
  cut(4);
}
__device__ __forceinline__ uint32_t prmt(uint32_t a, uint32_t b, uint32_t sel) {
  uint32_t d;
  asm("prmt.b32 %0, %1, %2, %3;" : "=r"(d) : "r"(a), "r"(b), "r"(sel));
  return d;
}
__device__ __forceinline__ uint32_t ballot_bit(uint32_t x, uint32_t bit) {
  uint32_t d;
  asm volatile("{\n.reg .pred p;\n.reg .u32 t;\nand.b32 t, %1, %2;\nsetp.ne.u32 p, t, 0;\nvote.sync.ballot.b32 %0, p, 0xffffffff;\n}\n"
               : "=r"(d) : "r"(x), "r"(bit));
  return d;
}
__device__ __forceinline__ uint4 load_mask(const void* mask, uint32_t b, uint32_t i) {
  uint4 m;
  asm volatile("ld.global.nc.L1::no_allocate.v4.u32 {%0,%1,%2,%3}, [%4];"
               : "=r"(m.x), "=r"(m.y), "=r"(m.z), "=r"(m.w) : "l"(reinterpret_cast<const uint4*>(mask) + (b * 25u + i)));
  return m;
}
__device__ __forceinline__ uint32_t nonzero_as_one(uint32_t x) {
  uint32_t d;
  asm("set.neu.bf16x2.bf16x2 %0, %1, %2;" : "=r"(d) : "r"(x), "r"(0u));
  return d;
}
__device__ __forceinline__ void cp_async_arrive_noinc(uint32_t bar) {
  asm volatile("cp.async.mbarrier.arrive.noinc.shared::cta.b64 [%0];" :: "r"(bar) : "memory");
}
__device__ __forceinline__ void ldsm_x4(uint32_t addr, uint32_t& r0, uint32_t& r1, uint32_t& r2, uint32_t& r3) {
  asm volatile("ldmatrix.sync.aligned.m8n8.x4.shared.b16 {%0,%1,%2,%3}, [%4];"
               : "=r"(r0), "=r"(r1), "=r"(r2), "=r"(r3) : "r"(addr) : "memory");
}
__device__ __forceinline__ void ldsm_x4_t(uint32_t addr, uint32_t& r0, uint32_t& r1, uint32_t& r2, uint32_t& r3) {
  asm volatile("ldmatrix.sync.aligned.m8n8.x4.trans.shared.b16 {%0,%1,%2,%3}, [%4];"
               : "=r"(r0), "=r"(r1), "=r"(r2), "=r"(r3) : "r"(addr) : "memory");
}
__device__ __forceinline__ void stsm_x4_t(uint32_t addr, uint32_t r0, uint32_t r1, uint32_t r2, uint32_t r3) {
  asm volatile("stmatrix.sync.aligned.m8n8.x4.trans.shared.b16 [%0], {%1,%2,%3,%4};"
               :: "r"(addr), "r"(r0), "r"(r1), "r"(r2), "r"(r3) : "memory");
}
__device__ __forceinline__ uint32_t hfma2_bf16(uint32_t a, uint32_t b, uint32_t c) {
  uint32_t d;
  asm volatile("fma.rn.bf16x2 %0, %1, %2, %3;" : "=r"(d) : "r"(a), "r"(b), "r"(c));
  return d;
}
__device__ __forceinline__ uint32_t pack_bf16(float lo, float hi) {
  uint32_t d;
  asm("cvt.rn.bf16x2.f32 %0, %1, %2;" : "=r"(d) : "f"(hi), "f"(lo));
  return d;
}
__device__ __forceinline__ uint32_t lds32(uint32_t a) {
  uint32_t v; asm volatile("ld.shared.u32 %0, [%1];" : "=r"(v) : "r"(a) : "memory"); return v;
}
__device__ __forceinline__ uint32_t lds16(uint32_t a) {
  uint32_t v; asm volatile("ld.shared.u16 %0, [%1];" : "=r"(v) : "r"(a) : "memory"); return v;
}
__device__ __forceinline__ void sts32(uint32_t a, uint32_t v) {
  asm volatile("st.shared.u32 [%0], %1;" :: "r"(a), "r"(v) : "memory");
}
__device__ __forceinline__ void sts16(uint32_t a, uint32_t v) {
  asm volatile("st.shared.u16 [%0], %1;" :: "r"(a), "h"((unsigned short)v) : "memory");
}
__device__ __forceinline__ void sts8(uint32_t a, uint32_t v) {
  asm volatile("st.shared.u8 [%0], %1;" :: "r"(a), "r"(v) : "memory");
}
constexpr uint32_t DESC_ROWS = 0x40000040u, DESC_HALVES = 0x80000020u;
__device__ __forceinline__ uint32_t desc_lo(uint32_t addr) { return ((addr & 0x3FFFF) >> 4) | (1u << 16); }

__device__ __forceinline__ uint4 lds128(uint32_t a) {
  uint4 v;
  asm volatile("ld.shared.v4.u32 {%0,%1,%2,%3}, [%4];" : "=r"(v.x), "=r"(v.y), "=r"(v.z), "=r"(v.w) : "r"(a) : "memory");
  return v;
}
__device__ __forceinline__ void sts128(uint32_t a, uint4 v) {
  asm volatile("st.shared.v4.u32 [%0], {%1,%2,%3,%4};" :: "r"(a), "r"(v.x), "r"(v.y), "r"(v.z), "r"(v.w) : "memory");
}
__device__ __forceinline__ void prefetch_l2(const void* p, uint32_t bytes) {
  asm volatile("cp.async.bulk.prefetch.L2.global [%0], %1;" :: "l"(p), "r"(bytes) : "memory");
}

__device__ __forceinline__ void mma_fence() { asm volatile("wgmma.fence.sync.aligned;" ::: "memory"); }
__device__ __forceinline__ void mma_commit() { asm volatile("wgmma.commit_group.sync.aligned;" ::: "memory"); }
template<bool FIRST>
__device__ __forceinline__ void hmma(float (&c)[4], const uint32_t* a, uint32_t b0, uint32_t b1) {
  if (FIRST)
    asm volatile("mma.sync.aligned.m16n8k16.row.col.f32.bf16.bf16.f32 {%0,%1,%2,%3}, {%4,%5,%6,%7}, {%8,%9}, {%10,%10,%10,%10};"
                 : "=f"(c[0]), "=f"(c[1]), "=f"(c[2]), "=f"(c[3]) : "r"(a[0]), "r"(a[1]), "r"(a[2]), "r"(a[3]), "r"(b0), "r"(b1), "f"(0.f));
  else
    asm volatile("mma.sync.aligned.m16n8k16.row.col.f32.bf16.bf16.f32 {%0,%1,%2,%3}, {%4,%5,%6,%7}, {%8,%9}, {%0,%1,%2,%3};"
                 : "+f"(c[0]), "+f"(c[1]), "+f"(c[2]), "+f"(c[3]) : "r"(a[0]), "r"(a[1]), "r"(a[2]), "r"(a[3]), "r"(b0), "r"(b1));
}
__device__ __forceinline__ void tanh_some(float* d, int i0, int i1) {
#pragma unroll
  for (int i = i0; i < i1; i++) asm volatile("tanh.approx.f32 %0, %0;" : "+f"(d[i ^ 2]));
}
__device__ __forceinline__ uint32_t mix(const float* d, int i, float r) {
  uint32_t p;
  asm volatile("{\n.reg .f32 x, y;\nfma.rn.f32 x, %3, %5, %1;\nfma.rn.f32 y, %4, %5, %2;\ncvt.rn.bf16x2.f32 %0, y, x;\n}\n"
               : "=r"(p) : "f"(d[4 * i]), "f"(d[4 * i + 1]), "f"(d[4 * i + 2]), "f"(d[4 * i + 3]), "f"(r));
  return p;
}
__device__ __forceinline__ uint32_t sums_at(uint32_t d) { return S_OUT + (d ^ ((d >> 3) & 1)) * 16; }
template<int K> __device__ __forceinline__ uint32_t keep(uint32_t x) { return K ? __shfl_sync(0xffffffffu, x, 0) : x; }

__global__ void __launch_bounds__(NTHREADS, 1)
din_kernel(const __nv_bfloat16* __restrict__ mask, const __nv_bfloat16* __restrict__ target, int B, int grid,
           uint32_t pf_mask, uint32_t pf_tgt, const __nv_bfloat16* __restrict__ w1, const __nv_bfloat16* __restrict__ hist,
           const __nv_bfloat16* __restrict__ b1, const __nv_bfloat16* __restrict__ w2,
           const __nv_bfloat16* __restrict__ b2, __nv_bfloat16* __restrict__ out, unsigned int* counter, int pace16,
           int slow_pace, int slow_from) {
  {
    const char* pm = reinterpret_cast<const char*>(mask) + (size_t)blockIdx.x * pf_mask;
    const char* pt = reinterpret_cast<const char*>(target) + (size_t)blockIdx.x * pf_tgt;
    const uint32_t o = threadIdx.x * 128;
    asm volatile("{\n.reg .pred p;\nsetp.lt.u32 p, %1, %2;\n@p prefetch.global.L2 [%0];\n}\n" :: "l"(pm + o), "r"(o), "r"(pf_mask));
    asm volatile("{\n.reg .pred p;\nsetp.lt.u32 p, %1, %2;\n@p prefetch.global.L2 [%0];\n}\n" :: "l"(pt + o), "r"(o), "r"(pf_tgt));
  }
  extern __shared__ unsigned char smem_raw[];
  const uint32_t sb = (smem_u32(smem_raw) + 1023u) & ~1023u;
  const int tid = threadIdx.x, lane = tid & 31;
  const int warp = __shfl_sync(0xffffffffu, tid >> 5, 0);
#define ACT NCW
  const int bstep = ACT * grid;

  STAMP(0);
  if (warp < NCW * 4) {
    const int wg = warp >> 2, w = warp & 3;
    const int g = lane >> 2;
    const uint32_t ring = sb + wg * RING_BYTES;
    const bool active = wg * grid + (int)blockIdx.x < B && wg < ACT;
    {
      const int t = tid & 127;
      const uint32_t dst = sb + ((t ^ ((t >> 3) & 7)) << 4);
      const char* src = reinterpret_cast<const char*>(w1) + t * 16;
#pragma unroll
      for (int i = 0; i < 4; i++) cp_async16(dst + w1_at(i) + wg * 2048, src + i * 8192 + wg * 2048);
      cp_async16(dst + w1_at(0) + wg * 8192 + 6144, src + wg * 8192 + 6144);
      if (wg == 0) cp_async16(dst + w1_at(3) + 6144, src + 3 * 8192 + 6144);
      if (lane < 8) {
        if (w == 0 && active) cp_async16(ring + R_TGT0 + lane * 16, target + (size_t)(wg * grid + blockIdx.x) * kD + lane * 8);
        if (w == 1 && wg < 2) cp_async16(ring + R_VEC + lane * 16, (wg ? w2 : b1) + lane * 8);
      }
    }
    if (w == 2) sts32(ring + R_SEL + lane * 4, 0x3e803e80u);
    uint32_t rb2;
    asm volatile("ld.global.nc.u16 %0, [%1];" : "=r"(rb2) : "l"(b2));
    asm volatile("setmaxnreg.inc.sync.aligned.u32 %0;" :: "n"(CONS_REGS));
    asm volatile("cp.async.wait_all;" ::: "memory");
    STAMP(5);
    asm volatile("bar.sync 1, %0;" :: "n"(NCW * 160) : "memory");
    float r;
    uint32_t cq, swap, half2, bf[4];
    {
      const uint32_t v2 = sb + RING_BYTES + R_VEC + ((lane & 24) * 2 + (lane & 7)) * 2;
      const float x = __uint_as_float(lds16(v2) << 16), y = __uint_as_float(lds16(v2 + 16) << 16);
      float c = x + y;
#pragma unroll
      for (int o = 16; o; o >>= 1) c += __shfl_xor_sync(0xffffffffu, c, o);
      c = 0.5f * c + __uint_as_float(rb2 << 16);
      const bool sw = fabsf(y) > fabsf(x);
      const float u = sw ? y : x, v = sw ? x : y;
      const bool off = !(fabsf(u) > fabsf(c) * 0x1p-40f);
      const float sc = off ? __uint_as_float(max(__float_as_uint(c) & 0x7f800000u, 8u << 23) - (4u << 23)) : 0.5f * u;
      float upto = fabsf(sc);
#pragma unroll
      for (int o = 2; o < 32; o *= 2) {
        const float z = __shfl_up_sync(0xffffffffu, upto, o);
        if (lane >= o) upto += z;
      }
      const float all = __shfl_sync(0xffffffffu, upto, 30 + (lane & 1));
      const float m = c / all;
      const float grid_ = __uint_as_float((__float_as_uint(2.0625f + 1.03125f * fabsf(m)) & 0x7f800000u) - (7u << 23));
      const float m0 = __fadd_rn(__fadd_rn(m, grid_ * 0x1.8p23f), grid_ * -0x1.8p23f);
      const float rest = fmaf(-m0, all, c);
      float q = (upto - 0.5f * fabsf(sc)) * grid_ < fabsf(rest) ? m0 + copysignf(grid_, rest) : m0;
      if (sc < 0.f) q = -q;
      const int own = 8 * w + g;
      r = __shfl_sync(0xffffffffu, off ? 0.f : v / u, own);
      cq = __shfl_sync(0xffffffffu, pack_bf16(q, q), own);
      swap = __shfl_sync(0xffffffffu, sw, own);
      half2 = __shfl_sync(0xffffffffu, off ? 0u : 0x3f003f00u, own);
      const int odd = (g ^ (g >> 1)) & 1;
#pragma unroll
      for (int i = 0; i < 4; i++)
        bf[i] = (__float_as_uint(__shfl_sync(0xffffffffu, sc, 8 * i + 2 * (lane & 3) + odd)) >> 16) << (16 * odd);
      if (warp == 0) {
        sts128(sb + SCALES + lane * 16, make_uint4(bf[0], bf[1], bf[2], bf[3]));
        asm volatile("bar.arrive 6, 160;" ::: "memory");
      }
    }
    const uint32_t nhalf2 = half2 ^ 0x80008000u, nzero2 = 0x80008000u;
    const uint32_t vec = sb + R_VEC + (16 * w + g) * 2;
    const float b1a = __uint_as_float(half2 << 16) * __uint_as_float(lds16(vec + (swap ? 16 : 0)) << 16);
    const float b1b = __uint_as_float(half2 << 16) * __uint_as_float(lds16(vec + (swap ? 0 : 16)) << 16);
    uint32_t wac[16], wd[16], wbc[16];
    {
      const int mi = lane >> 3, rr = lane & 7;
      const uint32_t a0 = sb + (8 * (mi >> 1) + rr) * 128 + (((2 * w + (mi & 1)) ^ rr) << 4);
#pragma unroll
      for (int ks = 0; ks < 4; ks++) {
        uint32_t A[4], Bm[4], C[4], Dm[4];
        ldsm_x4_t(a0 + ks * 2048 + w1_at(0), A[0], A[1], A[2], A[3]);
        ldsm_x4_t(a0 + ks * 2048 + w1_at(1), Bm[0], Bm[1], Bm[2], Bm[3]);
        ldsm_x4_t(a0 + ks * 2048 + w1_at(2), C[0], C[1], C[2], C[3]);
        ldsm_x4_t(a0 + ks * 2048 + w1_at(3), Dm[0], Dm[1], Dm[2], Dm[3]);
#pragma unroll
        for (int e = 0; e < 4; e++) {
          A[e] = hfma2_bf16(A[e], half2, hfma2_bf16(C[e], half2, nzero2));
          Bm[e] = hfma2_bf16(Bm[e], half2, hfma2_bf16(C[e], nhalf2, nzero2));
          Dm[e] = hfma2_bf16(Dm[e], half2, nzero2);
        }
#pragma unroll
        for (int e = 0; e < 4; e++) {
          wac[4 * ks + e] = swap ? A[e ^ 1] : A[e];
          wbc[4 * ks + e] = swap ? Bm[e ^ 1] : Bm[e];
          wd[4 * ks + e] = swap ? Dm[e ^ 1] : Dm[e];
        }
      }
    }
    asm volatile("fence.proxy.async.shared::cta;" ::: "memory");
    asm volatile("bar.sync 5, %0;" :: "n"(NCW * 128) : "memory");

    const uint32_t ln = __shfl_sync(0xffffffffu, lane, lane);
    const uint32_t meta = __shfl_sync(0xffffffffu, g & 1 ? 0xdd8888ddu : 0x88dddd88u, lane);
    const uint32_t zr = grid >> 20;
    const uint32_t sel = keep<K_SEL>(((ring + R_SEL) & 0x3FFFF) >> 4);
    const uint32_t rat = __shfl_sync(0xffffffffu, sums_at(8 * w + (lane & 7)) + (lane >> 3) * 512, lane);
    const uint32_t hi1c = DESC_ROWS + zr, hi2c = DESC_HALVES + zr;
    const uint32_t nu = __shfl_sync(0xffffffffu, lane >> 5, lane);
    const uint32_t barid = __shfl_sync(0xffffffffu, 2 + (tid >> 7), lane);
    const uint32_t toff = __shfl_sync(0xffffffffu, (lane & 24) << 1, lane);
    const uint32_t ost = __shfl_sync(0xffffffffu, w * 1024 + sums_at(lane), lane);
    if (active) {
      uint32_t t[8];
      auto load_t = [&](uint32_t ta) {
        ldsm_x4(ta + toff, t[0], t[1], t[2], t[3]);
        ldsm_x4(ta + toff + 64, t[4], t[5], t[6], t[7]);
      };
      load_t(ring + R_TGT0);
      STAMP(1);
      uint32_t hdr = keep<1>(ring), raw, cur = hdr + (R_SPARE - S_EMPTY);
      uint32_t x, nxt;
      auto peek_header = [&]() {
        nxt = hdr & H_NEXT;
        if (K_NX) asm volatile("" : "+r"(nxt));
        x = lds32(nxt + S_HDR + (K_NU ? nu : 0));
      };
      auto next_header = [&]() {
        asm volatile("{\n.reg .pred p;\n.reg .u32 n;\n.reg .s32 y;\n"
                     "xor.b32 y, %0, %2;\nsetp.ge.s32 p, y, 0;\n@p bra.uni FRESH;\n"
                     "mov.u32 n, 0;\n"
                     "AGAIN:\nadd.u32 n, n, 1;\nsetp.gt.u32 p, n, 0x1000000;\n@p trap;\nnanosleep.u32 32;\n"
                     "ld.shared.u32 %0, [%1];\nxor.b32 y, %0, %2;\nsetp.lt.s32 p, y, 0;\n@p bra.uni AGAIN;\n"
                     "FRESH:\n}\n" : "+r"(x) : "r"(nxt + S_HDR), "r"(hdr << 1) : "memory");
        if (!K_TOP) raw = __shfl_sync(0xffffffffu, x, 0);
      };
      peek_header();
      next_header();
      while (true) {
        __syncwarp();
        if (ln == 0) mbar_arrive(cur + S_EMPTY);
        cur = nxt;
        hdr = K_TOP ? __shfl_sync(0xffffffffu, x, 0) : raw;
        uint32_t we[16], bq[4];
        {
          float c[4][4];
          asm volatile("mma.sync.aligned.m16n8k16.row.col.f32.bf16.bf16.f32 {%0,%1,%2,%3}, {%4,%5,%6,%7}, {%8,%9}, {%10,%11,%12,%13};"
                       : "=f"(c[0][0]), "=f"(c[0][1]), "=f"(c[0][2]), "=f"(c[0][3])
                       : "r"(wbc[0]), "r"(wbc[1]), "r"(wbc[2]), "r"(wbc[3]), "r"(t[0]), "r"(t[1]), "f"(b1a), "f"(r), "f"(b1b), "f"(__uint_as_float(cq)));
#pragma unroll
          for (int i = 1; i < 4; i++) hmma<true>(c[i], wbc + 4 * i, t[2 * i], t[2 * i + 1]);
#pragma unroll
          for (int i = 0; i < 16; i++) we[i] = hfma2_bf16(t[i >> 1], wd[i], wac[i]);
#pragma unroll
          for (int i = 0; i < 4; i++) bq[i] = pack_bf16(c[i & 2][2 * (i & 1)], c[(i & 2) + 1][2 * (i & 1)]);
        }
        auto log_end = [&]() {
          LOGT(1);
        };
        auto chunk = [&](auto groups) {
          constexpr int N8 = decltype(groups)::value, KE = (N8 + 1) / 2, KA = KE - (N8 == 12 ? KL12 : KL);
          float d[4 * N8], o[16];
          uint32_t a[4 * KE];
          auto scores = [&](int i0, int i1) {
#pragma unroll
            for (int i = i0; i < i1; i++) {
              a[2 * i] = i < N8 ? mix(d, i, r) : 0;
              a[2 * i + 1] = i < N8 ? hfma2_bf16(a[2 * i], 0x3f803f80u, cq) : 0;
              if (N8 == 16) {
                uint32_t m = 0x3f803f80u;
                asm volatile("{\n.reg .pred p;\nsetp.ne.u32 p, %1, 0;\n@p ld.shared.u32 %0, [%2];\n}\n"
                             : "+r"(m) : "r"(hdr & H_GENERAL), "r"(cur + S_MASK + i * 16 + (ln & 3) * 4) : "memory");
                a[2 * i] = hfma2_bf16(a[2 * i], m, 0x80008000u);
                a[2 * i + 1] = hfma2_bf16(a[2 * i + 1], m, 0x80008000u);
              }
            }
          };
          const uint32_t lo = cur >> 4, lo1 = lo + K_LO * 0x10000, lo2 = lo + K_LO2 * 0x10000;
          const uint32_t hi1 = K_HI1 == 0 ? hi1c : K_HI1 == 1 ? DESC_ROWS + (cur >> 24) : DESC_ROWS + (lo >> 19);
          const uint32_t hi2 = K_HI2 == 0 ? hi2c : K_HI2 == 1 ? DESC_HALVES + (cur >> 24) : K_HI2 == 2 ? hi1 + (DESC_HALVES - DESC_ROWS) : DESC_HALVES + (lo >> 18);
          uint32_t oa = cur + ost;
          auto cut = [&]() {
            asm volatile("{\n.reg .pred p;\nsetp.ne.u32 p, %1, 0;\n@p mov.u32 %0, %%clock;\n}\n" : "+r"(oa) : "r"(zr) : "memory");
          };
          uint32_t at = lo1;
          auto step = [&](uint32_t base, int from, int to) {
            if (K_CH) asm volatile("add.u32 %0, %0, %1;" : "+r"(at) : "r"(to - from)); else at = base + to;
          };
          auto g2 = [&](int k) {
            step(lo2, k ? 128 * (k - 1) : 64 * NA + 6, 128 * k);
            if (k == 0) g2_first(o, a, at, meta, hi2); else g2_more(o, a + 4 * k, at, meta, hi2);
          };
          mma_fence();
          g1_bias<NA>(d, bq, sel);
          g1_bias<N8 - NA>(d + 4 * NA, bq, sel);
          mma_commit();
          mbar_wait(cur + S_FULL, hdr >> 31);
          LOGT(0);
          WSTAMP(0);
          mma_fence();
#pragma unroll
          for (int k = 0; k < 4; k++) { if (k) step(lo1, 2 * k - 2, 2 * k); g1_step<NA>(d, we + 4 * k, at, hi1); }
          mma_commit();
#pragma unroll
          for (int k = 0; k < 4; k++) {
            step(lo1, k ? 64 * NA + 2 * k - 2 : 6, 64 * NA + 2 * k);
            g1_step<N8 - NA>(d + 4 * NA, we + 4 * k, at, hi1);
          }
          mma_commit();
          mma_wait<1>(d, Int<NA>());
          WSTAMP(1);
          if (LPOS == 3) peek_header();
          tanh_some(d, 0, 4 * NA);
          scores(0, NA - 1);
          cut();
          mma_wait<0>(d + 4 * NA, Int<N8 - NA>());
          WSTAMP(2);
          load_t(cur + S_TGT);
          if (LPOS == 0) peek_header();
          constexpr int T0 = 8 * KA + D0 < 4 * N8 ? 8 * KA + D0 : 4 * N8;
          tanh_some(d, 4 * NA, T0);
          scores(NA - 1, 2 * KA);
          mma_fence();
#pragma unroll
          for (int k = 0; k < KA; k++) {
            g2(k);
            if (k == KA - KC) cut();
          }
          mma_commit();
          if (LPOS == 2) peek_header();
          tanh_some(d, T0, 4 * N8);
          scores(2 * KA, 2 * KE);
          mma_fence();
#pragma unroll
          for (int k = KA; k < KE; k++) g2(k);
          mma_commit();
          if (LPOS == 1) peek_header();
          next_header();
          mma_wait<0>(o, Int<4>());
          WSTAMP(7);
#pragma unroll
          for (int e = 0; e < 2; e++)
            stsm_x4_t(oa + e * 512, pack_bf16(o[2 * e], o[2 * e + 1]), pack_bf16(o[2 * e + 4], o[2 * e + 5]),
                      pack_bf16(o[2 * e + 8], o[2 * e + 9]), pack_bf16(o[2 * e + 12], o[2 * e + 13]));
          log_end();
        };
        if (hdr & H_13) { chunk(Int<13>()); if (hdr & (H_FINAL | H_12)) break; }
        else if (hdr & H_12) { chunk(Int<12>()); if (hdr & (H_FINAL | H_14)) break; }
        else if (hdr & H_14) { chunk(Int<14>()); if (hdr & (H_FINAL | H_GENERAL)) break; }
        else { chunk(Int<16>()); if (hdr & H_FINAL) break; }
      }
      asm volatile("bar.sync %0, 128;" :: "r"(barid) : "memory");
      uint32_t u[8], l2 = ln;
      ldsm_x4(cur + rat, u[0], u[1], u[2], u[3]);
      ldsm_x4(cur + rat + 2048, u[4], u[5], u[6], u[7]);
      asm volatile("{\n.reg .pred p;\nsetp.ne.u32 p, %1, 0;\n@p mov.u32 %0, %%clock;\n}\n" : "+r"(l2) : "r"(zr) : "memory");
      __nv_bfloat16* dst = out + (x * kD + 8 * w + (l2 >> 2) + (l2 & 1) * 32);
      uint32_t skip = (l2 & 2) | (~hdr & H_SELF);
      asm volatile("{\n.reg .pred p;\nsetp.ne.u32 p, %2, 0;\n@p mov.u32 %0, %%clock;\n}\n" : "+r"(skip), "+l"(dst) : "r"(zr) : "memory");
      float c[4], e[4];
      hmma<true>(c, u, bf[0], bf[1]);
      hmma<true>(e, u + 4, bf[2], bf[3]);
      asm volatile("{\n.reg .pred p;\nsetp.eq.u32 p, %2, 0;\n@p st.global.u16 [%0], %1;\n}\n"
                   :: "l"(dst), "h"(__bfloat16_as_ushort(__float2bfloat16((c[0] + c[3]) + (e[0] + e[3])))), "r"(skip) : "memory");
      if (!(hdr & H_SELF) && ln == 0) mbar_arrive(cur + S_EMPTY);
    }
    STAMP(4);
  } else {
    const int pw = warp - NCW * 4;
    const uint32_t ring = sb + pw * RING_BYTES;
    asm volatile("setmaxnreg.dec.sync.aligned.u32 %0;" :: "n"(PROD_REGS));
    if (pw < NCW) {
      int b = pw * grid + blockIdx.x, bn = b + bstep;
      uint4 mw = load_mask(mask, min(b, B - 1), min(lane, 24));
      if (lane == 0) {
#pragma unroll
        for (int i = 0; i < NSLOT; i++) {
          mbar_init(ring + i * SLOT_BYTES + S_FULL, 34);
          mbar_init(ring + i * SLOT_BYTES + S_EMPTY, 4);
          mbar_arrive(ring + i * SLOT_BYTES + S_FULL);
          sts32(ring + i * SLOT_BYTES + S_HDR, 0x80000000u);
        }
        mbar_init(ring + R_SPARE, 5);
        sts32(ring + R_STOP, pw < ACT ? 0 : ring);
      }
      sts32(sb + R_PACE + lane * 4, 0);
      asm volatile("bar.arrive 1, %0;" :: "n"(NCW * 160) : "memory");
      asm volatile("bar.arrive 6, 160;" ::: "memory");
      if (pw >= ACT) return;
      const uint32_t list = ring + R_LIST;
      uint32_t lt;
      asm("mov.u32 %0, %%lanemask_lt;" : "=r"(lt));
      const uint32_t ln = __shfl_sync(0xffffffffu, lane, lane);
      const uint32_t r4 = (ln >> 3) * 4, c16 = (ln & 7) * 16, l25 = min(ln, 24u);
      const uint32_t pick = ln < 25 ? 0xeca8 : 0x9999;
      uint32_t dst[4];
#pragma unroll
      for (int i = 0; i < 4; i++) dst[i] = ring + (r4 + i) * 128 + (c16 ^ (((r4 + i) & 7) << 4));
      uint64_t pol;
      asm("createpolicy.fractional.L2::evict_first.b64 %0, 1.0;" : "=l"(pol));
      uint32_t sa = ring, phase = 1;
      const uint32_t wrap = (uint32_t)(max(B - NSTATIC * bstep, 0) + bstep - 1);
      auto next_slot = [&]() {
        const bool wrapped = sa == ring + (NSLOT - 1) * SLOT_BYTES;
        const int step = wrapped ? -(NSLOT - 1) * SLOT_BYTES : SLOT_BYTES;
        sa += step;
        phase ^= wrapped;
#pragma unroll
        for (int i = 0; i < 4; i++) dst[i] += step;
      };
      uint32_t claimer = ln;
      uint32_t drawn;
      auto draw = [&]() {
        drawn = B;
        asm volatile("{\n.reg .pred p;\nsetp.eq.u32 p, %3, 0;\n@p atom.global.inc.u32 %0, [%1], %2;\n}\n"
                     : "+r"(drawn) : "l"(counter), "r"(wrap), "r"(claimer) : "memory");
      };
      if (b >= B) draw();
      int n = kL, mean16 = 8 * kL;
      while (b < B) {
        const uint32_t e0 = nonzero_as_one(mw.x), e1 = nonzero_as_one(mw.y);
        const uint32_t e2 = nonzero_as_one(mw.z), e3 = nonzero_as_one(mw.w);
        const uint32_t nonbin = (e0 ^ mw.x) | (e1 ^ mw.y) | (e2 ^ mw.z) | (e3 ^ mw.w);
        const uint32_t sA = prmt(e0, e1, pick), sB = prmt(e2, e3, pick);
        const uint32_t pA = (sA & 0x01010101u) * 0x01010101u;
        const uint32_t pB = ((sB & 0x01010101u) + (pA >> 24)) * 0x01010101u;
        uint32_t pos = 0;
        n = 0;
#pragma unroll
        for (int k = 0; k < 4; k++) {
          const uint32_t bal = ballot_bit(pB, 0x01000000u << k);
          pos += __popc(bal & lt) << k;
          n += __popc(bal) << k;
        }
        const uint32_t general = __any_sync(0xffffffffu, nonbin != 0);
        const uint32_t aA = (pA + pos * 0x01010101u) | ~sA, aB = (pB + pos * 0x01010101u) | ~sB;
#pragma unroll
        for (int i = 0; i < 8; i++) sts8(list - 1 + prmt(i < 4 ? aA : aB, 0, 0x4440 + (i & 3)), 8 * ln + i);
        __syncwarp();

        const uint64_t src = reinterpret_cast<uint64_t>(hist) + (uint64_t)b * (kL * kD * 2);
        const bool no_carry = (uint32_t)src <= 0xffffffffu - kL * kD * 2;
        auto begin_fill = [&](uint32_t h, uint32_t part, int nc, int bt, auto extra) {
          LOGT(0);
          mbar_wait(sa + S_EMPTY, phase);
          if (bt >= B) h |= part ? H_FINAL : H_FINAL | H_SELF;
          extra();
          {
            const bool wrapped = sa == ring + (NSLOT - 1) * SLOT_BYTES;
            sts32(sa + S_HDR, (h | (wrapped ? ring + 0x40000000u : sa + SLOT_BYTES)) ^ ((phase - 1) & 0xc0000000u));
          }
          sts32(sa + S_ROW + phase * 4, b | part);
          asm volatile("{\n.reg .pred p;\nsetp.eq.u32 p, %1, 0;\n@p mbarrier.arrive.shared::cta.b64 _, [%0];\n}\n"
                       :: "r"(sa + S_FULL), "r"(ln) : "memory");
          mean16 += nc - (mean16 >> 4);
          asm volatile("{\n.reg .u32 f, c;\n.reg .s32 d;\n.reg .pred p;\n"
                       "mov.u32 c, %%globaltimer_lo;\n"
                       "red.shared.max.u32 [%0], c;\n"
                       "atom.shared.add.u32 f, [%0], %1;\n"
                       "shfl.sync.idx.b32 f, f, 0, 31, 0xffffffff;\n"
                       "SPIN:\n"
                       "mov.u32 c, %%globaltimer_lo;\n"
                       "sub.s32 d, c, f;\n"
                       "setp.gt.u32 p, d, %2;\n"
                       "@p bra.uni SPIN;\n}\n" :: "r"(sb + R_PACE + ln * 4), "r"((bn >= slow_from ? mean16 * slow_pace : nc * pace16) >> 8), "r"(~(pace16 * (CHUNK / 64))) : "memory");
          if (!(part & ROW_REST)) {
            mw = load_mask(mask, min(bn, B - 1), l25);
            draw();
          }
          LOGT(1);
          asm volatile("cp.async.ca.shared.global [%0], [%1], 4;"
                       :: "r"(sa + S_TGT + ln * 4), "l"(reinterpret_cast<const uint32_t*>(target) + ((uint32_t)min(bt, B - 1) * 32u + ln)) : "memory");
        };
        auto end_fill = [&](int nc) {
          cp_async_arrive_noinc(sa + S_FULL);
          next_slot();
          LOGT(2);
        };
        auto usual = [&]() {
          uint32_t idx[7];
#pragma unroll
          for (int t = 0; t < 7; t++) idx[t] = lds32(list + r4 + t * 16);
          begin_fill(size_flag(n), 0, n, bn, [](){});
          const int left = n - r4;
          const uint32_t base = (uint32_t)src + c16;
          uint64_t a[NPAIR];
#pragma unroll
          for (int i = 0; i < NPAIR; i++) a[i] = (uint64_t)((uint32_t)(src >> 32) + (ln >> 5)) << 32;
          cp_group<0, false>(dst, a, idx[0], base, left, pol, claimer);
          cp_group<1, false>(dst, a, idx[1], base, left, pol, claimer);
          cp_group<2, false>(dst, a, idx[2], base, left, pol, claimer);
          cp_group<3, false>(dst, a, idx[3], base, left, pol, claimer);
          cp_group<4, true>(dst, a, idx[4], base, left, pol, claimer);
          cp_group<5, true>(dst, a, idx[5], base, left, pol, claimer);
          if (n > 96) {
            cp_group<6, true>(dst, a, idx[6], base, left, pol, claimer);
            if (n > 112) cp_group<7, true>(dst, a, lds32(list + r4 + 112), base, left, pol, claimer);
          }
          end_fill(n);
        };
        auto other = [&]() {
          int r0 = 0, nc = n <= CHUNK ? n : n <= 160 ? 64 : 96;
#pragma unroll 1
          do {
            const bool more = r0 + nc < n;
            begin_fill(general ? H_GENERAL : size_flag(max(nc, 64)), (more ? ROW_MORE : 0u) | (r0 ? ROW_REST : 0u), nc, more ? b : bn, [&]() {
#pragma unroll 1
              for (int z = ln; general && z < CHUNK; z += 32) {
                uint32_t v = 0;
                if (z < nc) {
                  uint32_t row;
                  asm volatile("ld.shared.u8 %0, [%1];" : "=r"(row) : "r"(list + r0 + z) : "memory");
                  v = __bfloat16_as_ushort(mask[(size_t)b * kL + row]);
                }
                sts16(sa + S_MASK + z * 2, v);
              }
              __syncwarp();
            });
            uint32_t rows4 = lds32(list + r0 + r4);
#pragma unroll 1
            for (int z = 0; z < CHUNK; z += 16) {
              const uint32_t now = rows4;
              rows4 = lds32(list + r0 + r4 + z + 16);
#pragma unroll
              for (int i = 0; i < 4; i++)
                asm volatile("{\n.reg .pred p;\nsetp.ge.s32 p, %2, %3;\ncp.async.cg.shared.global [%0], [%1], 16, p;\n}\n"
                             :: "r"(dst[i] + z * 128), "l"(src + c16 + prmt(now, 0, 0x4440 + i) * 128), "r"(z + r4 + i), "r"(nc) : "memory");
            }
            end_fill(nc);
            r0 += nc;
            nc = n - nc;
          } while (r0 < n);
        };
        if (n < 64 || n > CHUNK || !no_carry || general) other(); else usual();
        if (bn >= B) break;
        b = bn;
        bn = __shfl_sync(0xffffffffu, drawn, 0) + NSTATIC * bstep;
        if (bn >= B) claimer = 1;
      }
      STAMP(3);
      sts32(sa + S_HDR, b | (phase ^ 1) << 31);
      if (n <= CHUNK) {
#pragma unroll 1
        for (int i = 1; i < 2 * NSLOT; i++) next_slot();
      }
      sts32(ring + R_STOP, sa + (phase ^ 1));
      asm volatile("cp.async.wait_all;" ::: "memory");
      STAMP(4);
    } else {
      uint32_t due = clock();
      int s0 = NSTATIC * bstep + (PF_EARLY * grid + blockIdx.x) * PF_ROWS;
      auto prefetch = [&]() {
        const int cnt = min(PF_ROWS, B - s0);
        if (lane == 0) {
          prefetch_l2(mask + (size_t)s0 * kL, cnt * kL * 2);
          prefetch_l2(target + (size_t)s0 * kD, cnt * kD * 2);
        }
        s0 += grid * PF_ROWS;
      };
#pragma unroll 1
      for (int j = PF_EARLY; j < PF_FAST && s0 < B; j++) {
        while ((int)(due - (uint32_t)clock()) > 0) {}
        prefetch();
        due += PF_CYCLES;
      }
      due += (PF_FAST - 1) * PF_SLOW - (PF_FAST - PF_EARLY) * PF_CYCLES + (blockIdx.x & 255) * (PF_SLOW / 256);
      asm volatile("bar.sync 6, 160;" ::: "memory");
      constexpr uint32_t WHERE = 0x3ffff;
      const uint32_t mine = __shfl_sync(0xffffffffu, sb + min(lane, NCW - 1) * RING_BYTES, lane);
      uint32_t at = mine | ~WHERE;
      const uint32_t ln = __shfl_sync(0xffffffffu, lane, lane);
      const uint32_t rd = __shfl_sync(0xffffffffu, sums_at(2 * (lane & 7)) + (lane >> 3) * 512, lane);
      uint4 bf = lds128(sb + SCALES + lane * 16);
      bf.x += grid >> 20;
      bf.z += grid >> 20;
      uint32_t* const dst = reinterpret_cast<uint32_t*>(out) + ((lane & 1) * 16 + (lane & 2) * 4 + (lane >> 2));
      uint32_t idle = 0;
#pragma unroll 1
      while (true) {
        const uint32_t go = __reduce_max_sync(0xffffffffu, mbar_test((at & (WHERE - 1)) + S_EMPTY, at & 1) ? at : 0u);
        if (go) {
          const uint32_t sa = go & (WHERE - 1);
          const uint32_t row = lds32(sa + S_ROW + 4 - (go & 1) * 4);
          RSTAMP(0);
          uint32_t u[8][4];
#pragma unroll
          for (int i = 0; i < 8; i++) ldsm_x4(((sa + rd) ^ (i & 1) * 16) + (i & 2) * 128 + (i >> 2) * 2048, u[i][0], u[i][1], u[i][2], u[i][3]);
          if (RCUT) asm volatile("{\n.reg .pred p;\nsetp.eq.u32 p, %1, 0;\n@p mov.u32 %0, %%clock;\n}\n" : "+r"(idle) : "r"(sa) : "memory");
          float c[4][4];
#pragma unroll
          for (int j = 0; j < 4; j++) hmma<true>(c[j], u[j], bf.x, bf.y);
#pragma unroll
          for (int j = 0; j < 4; j++) hmma<false>(c[j], u[4 + j], bf.z, bf.w);
          RSTAMP(3);
          float e0 = c[0][0] + c[0][3], e1 = c[1][0] + c[1][3];
          if (ln & 2) { e0 = c[2][0] + c[2][3]; e1 = c[3][0] + c[3][3]; }
          __syncwarp();
          if (ln == 0) mbar_arrive(sa + S_FULL);
          if (at == go) at = (sa == mine + (NSLOT - 1) * SLOT_BYTES ? (at - (NSLOT - 1) * SLOT_BYTES) ^ 1 : at + SLOT_BYTES) - (WHERE + 1);
          if (__builtin_expect(row >= ROW_REST, 0)) {
            const uint32_t carry = __reduce_max_sync(0xffffffffu, mine <= sa ? mine : 0u) + R_CARRY + ln * 8;
            if (row & ROW_REST) { e0 += __uint_as_float(lds32(carry)); e1 += __uint_as_float(lds32(carry + 4)); }
            sts32(carry, __float_as_uint(e0));
            sts32(carry + 4, __float_as_uint(e1));
          }
          if (row < ROW_MORE) dst[(row & (ROW_REST - 1)) * 32] = pack_bf16(e0, e1);
        } else {
          if (__all_sync(0xffffffffu, lds32(mine + R_STOP) == (at & WHERE))) break;
          if (++idle > 0x4000000) __trap();
          if (s0 < B && (int)(due - (uint32_t)clock()) <= 0) { prefetch(); due += PF_SLOW; }
          if (RED_SLEEP) __nanosleep(RED_SLEEP);
        }
      }
    }
  }
}

}

extern "C" void kernel_launch(void* const* d_in, const int* in_sizes, int n_in, void* d_out, int out_size) {
  const __nv_bfloat16* target = (const __nv_bfloat16*)d_in[0];
  const __nv_bfloat16* hist = (const __nv_bfloat16*)d_in[1];
  const __nv_bfloat16* mask = (const __nv_bfloat16*)d_in[2];
  const __nv_bfloat16* w1 = (const __nv_bfloat16*)d_in[3];
  const __nv_bfloat16* b1 = (const __nv_bfloat16*)d_in[4];
  const __nv_bfloat16* w2 = (const __nv_bfloat16*)d_in[5];
  const __nv_bfloat16* b2 = (const __nv_bfloat16*)d_in[6];
  const int B = in_sizes[0] / din::kD;
  if (B <= 0) return;
  static int sms = 0, pace = 0;
  static unsigned int* counter = nullptr;
  if (sms == 0) {
    int dev = 0, khz = 0, bits = 0;
    cudaGetDevice(&dev);
    cudaDeviceGetAttribute(&sms, cudaDevAttrMultiProcessorCount, dev);
    cudaDeviceGetAttribute(&khz, cudaDevAttrMemoryClockRate, dev);
    cudaDeviceGetAttribute(&bits, cudaDevAttrGlobalMemoryBusWidth, dev);
    if (khz > 0 && bits > 0) pace = (int)(16.0 * 128.0 * sms / (khz * 1e-6 * 2.0 * bits / 8.0));
    if (pace > 256) pace = 0;
    cudaGetSymbolAddress((void**)&counter, din::g_next);
    cudaFuncSetAttribute(din::din_kernel, cudaFuncAttributeMaxDynamicSharedMemorySize, din::SMEM_BYTES);
  }
  const long long early = (long long)(din::NSTATIC * NCW + PF_EARLY * PF_ROWS) * sms, line = 128LL * sms;
  long long pf_mask = (early * din::kL * 2 + line - 1) / line, pf_tgt = early * din::kD * 2 / line;
  if (pf_mask > (long long)B * din::kL * 2 / line) pf_mask = (long long)B * din::kL * 2 / line;
  if (pf_tgt > (long long)B * din::kD * 2 / line) pf_tgt = (long long)B * din::kD * 2 / line;
  din::din_kernel<<<sms, din::NTHREADS, din::SMEM_BYTES>>>(mask, target, B, sms, (uint32_t)pf_mask * 128, (uint32_t)pf_tgt * 128,
                                                          w1, hist, b1, w2, b2, (__nv_bfloat16*)d_out, counter, pace * 16,
                                                          pace + pace * SLOW_BY / 80, B - SLOW_ROUNDS * NCW * sms);
}
```

```cpp
#include <cuda_runtime.h>
#include <cuda_bf16.h>
#include <stdint.h>

namespace din {

constexpr int kL = 200, kD = 64;
#define NCW 3
#define NSLOT 3
constexpr int CHUNK = 128;
constexpr int NTHREADS = NCW * 128 + 128;
#define PREGS 56
#define CREGS 152
constexpr int PROD_REGS = PREGS, CONS_REGS = CREGS;
#define PF_ROWS 8
#define PF_FAST 10
#define PF_SLOW 2000
#define PF_CYCLES 280
#define RED_SLEEP 100
#define K_SEL 1
#define K_LO2 2
#define K_HI1 2
#define K_HI2 2
#define K_NX 0
#define K_BAR 1
#define K_TOP 1
#define NA 4
#define KL 2
#define S0 1
#define D0 5
#define KC 4
#define PF_EARLY 3
#define SLOW_ROUNDS 5
#define SLOW_BY 13
constexpr int NSTATIC = 2;
constexpr int S_TGT = CHUNK * 128;
constexpr int S_HDR = S_TGT + 128;
constexpr int S_FULL = S_HDR + 8;
constexpr int S_EMPTY = S_HDR + 16;
constexpr int S_ROW = S_HDR + 24;
constexpr int S_MASK = S_TGT + 256;
constexpr int S_OUT = S_TGT + 1024;
constexpr int SLOT_BYTES = S_OUT + 4096;
constexpr int RING_BYTES_ = NSLOT * SLOT_BYTES;
constexpr int R_PACE = 2 * RING_BYTES_ + S_TGT + 768;
constexpr int R_START = S_HDR + 32;
constexpr int R_STOP = S_HDR + 44;
constexpr int R_LIST = S_TGT + 512;
constexpr int R_VEC = S_TGT + 768;
constexpr int R_SEL = S_TGT + 896;
constexpr int R_CARRY = SLOT_BYTES + S_TGT + 512;
constexpr int R_TGT0 = (NSLOT - 1) * SLOT_BYTES + S_OUT;
constexpr int RING_BYTES = NSLOT * SLOT_BYTES;
constexpr int SCALES = NCW * RING_BYTES + 32768;
constexpr int SMEM_BYTES = SCALES + 512 + 1024;
__device__ constexpr int w1_at(int i) { return NCW * RING_BYTES + i * 8192; }
static_assert(SMEM_BYTES <= 232448, "shared memory");
constexpr uint32_t H_12 = 0x1f, H_13 = 0x20, H_14 = 0x40, H_15 = 0x80, H_16 = 0x100;
constexpr uint32_t H_GENERAL = 1u << 18, H_FINAL = 1u << 19, H_SELF = 1u << 20, H_NEXT = 0x3fc3fc00;
__device__ __forceinline__ uint32_t size_flag(int rows) { return 1u << ((rows - 57) >> 3); }
constexpr uint32_t ROW_REST = 1u << 30, ROW_MORE = 1u << 31;

__device__ unsigned int g_next;

#define STR2(x) #x
#define STR(x) STR2(x)
template<int V> struct Int { static constexpr int value = V; };
template<int G> __device__ __forceinline__ void g1_bias(float* d, const uint32_t (&bq)[4], uint32_t loSel);
template<int G> __device__ __forceinline__ void g1_step(float* d, const uint32_t* a, uint32_t loH, uint32_t hiH);
template<> __device__ __forceinline__ void g1_bias<4>(float* d, const uint32_t (&bq)[4], uint32_t loSel) {
  asm volatile("{\n.reg .b64 db;\n.reg .b32 zr;\n"
    "mov.b32 zr, 0;\nmov.b64 db, {%20, zr};\n"
    "wgmma.mma_async.sync.aligned.m64n32k16.f32.bf16.bf16 {%0, %1, %2, %3, %4, %5, %6, %7, %8, %9, %10, %11, %12, %13, %14, %15}, {%16, %17, %18, %19}, db, 0, 1, 1, 0;\n}\n"
    : "=f"(d[0]), "=f"(d[1]), "=f"(d[2]), "=f"(d[3]), "=f"(d[4]), "=f"(d[5]), "=f"(d[6]), "=f"(d[7]), "=f"(d[8]), "=f"(d[9]), "=f"(d[10]), "=f"(d[11]), "=f"(d[12]), "=f"(d[13]), "=f"(d[14]), "=f"(d[15])
    : "r"(bq[0]), "r"(bq[1]), "r"(bq[2]), "r"(bq[3]), "r"(loSel)
    : "memory");
}
template<> __device__ __forceinline__ void g1_bias<8>(float* d, const uint32_t (&bq)[4], uint32_t loSel) {
  asm volatile("{\n.reg .b64 db;\n.reg .b32 zr;\n"
    "mov.b32 zr, 0;\nmov.b64 db, {%36, zr};\n"
    "wgmma.mma_async.sync.aligned.m64n64k16.f32.bf16.bf16 {%0, %1, %2, %3, %4, %5, %6, %7, %8, %9, %10, %11, %12, %13, %14, %15, %16, %17, %18, %19, %20, %21, %22, %23, %24, %25, %26, %27, %28, %29, %30, %31}, {%32, %33, %34, %35}, db, 0, 1, 1, 0;\n}\n"
    : "=f"(d[0]), "=f"(d[1]), "=f"(d[2]), "=f"(d[3]), "=f"(d[4]), "=f"(d[5]), "=f"(d[6]), "=f"(d[7]), "=f"(d[8]), "=f"(d[9]), "=f"(d[10]), "=f"(d[11]), "=f"(d[12]), "=f"(d[13]), "=f"(d[14]), "=f"(d[15]), "=f"(d[16]), "=f"(d[17]), "=f"(d[18]), "=f"(d[19]), "=f"(d[20]), "=f"(d[21]), "=f"(d[22]), "=f"(d[23]), "=f"(d[24]), "=f"(d[25]), "=f"(d[26]), "=f"(d[27]), "=f"(d[28]), "=f"(d[29]), "=f"(d[30]), "=f"(d[31])
    : "r"(bq[0]), "r"(bq[1]), "r"(bq[2]), "r"(bq[3]), "r"(loSel)
    : "memory");
}
template<> __device__ __forceinline__ void g1_bias<9>(float* d, const uint32_t (&bq)[4], uint32_t loSel) {
  asm volatile("{\n.reg .b64 db;\n.reg .b32 zr;\n"
    "mov.b32 zr, 0;\nmov.b64 db, {%40, zr};\n"
    "wgmma.mma_async.sync.aligned.m64n72k16.f32.bf16.bf16 {%0, %1, %2, %3, %4, %5, %6, %7, %8, %9, %10, %11, %12, %13, %14, %15, %16, %17, %18, %19, %20, %21, %22, %23, %24, %25, %26, %27, %28, %29, %30, %31, %32, %33, %34, %35}, {%36, %37, %38, %39}, db, 0, 1, 1, 0;\n}\n"
    : "=f"(d[0]), "=f"(d[1]), "=f"(d[2]), "=f"(d[3]), "=f"(d[4]), "=f"(d[5]), "=f"(d[6]), "=f"(d[7]), "=f"(d[8]), "=f"(d[9]), "=f"(d[10]), "=f"(d[11]), "=f"(d[12]), "=f"(d[13]), "=f"(d[14]), "=f"(d[15]), "=f"(d[16]), "=f"(d[17]), "=f"(d[18]), "=f"(d[19]), "=f"(d[20]), "=f"(d[21]), "=f"(d[22]), "=f"(d[23]), "=f"(d[24]), "=f"(d[25]), "=f"(d[26]), "=f"(d[27]), "=f"(d[28]), "=f"(d[29]), "=f"(d[30]), "=f"(d[31]), "=f"(d[32]), "=f"(d[33]), "=f"(d[34]), "=f"(d[35])
    : "r"(bq[0]), "r"(bq[1]), "r"(bq[2]), "r"(bq[3]), "r"(loSel)
    : "memory");
}
template<> __device__ __forceinline__ void g1_bias<10>(float* d, const uint32_t (&bq)[4], uint32_t loSel) {
  asm volatile("{\n.reg .b64 db;\n.reg .b32 zr;\n"
    "mov.b32 zr, 0;\nmov.b64 db, {%44, zr};\n"
    "wgmma.mma_async.sync.aligned.m64n80k16.f32.bf16.bf16 {%0, %1, %2, %3, %4, %5, %6, %7, %8, %9, %10, %11, %12, %13, %14, %15, %16, %17, %18, %19, %20, %21, %22, %23, %24, %25, %26, %27, %28, %29, %30, %31, %32, %33, %34, %35, %36, %37, %38, %39}, {%40, %41, %42, %43}, db, 0, 1, 1, 0;\n}\n"
    : "=f"(d[0]), "=f"(d[1]), "=f"(d[2]), "=f"(d[3]), "=f"(d[4]), "=f"(d[5]), "=f"(d[6]), "=f"(d[7]), "=f"(d[8]), "=f"(d[9]), "=f"(d[10]), "=f"(d[11]), "=f"(d[12]), "=f"(d[13]), "=f"(d[14]), "=f"(d[15]), "=f"(d[16]), "=f"(d[17]), "=f"(d[18]), "=f"(d[19]), "=f"(d[20]), "=f"(d[21]), "=f"(d[22]), "=f"(d[23]), "=f"(d[24]), "=f"(d[25]), "=f"(d[26]), "=f"(d[27]), "=f"(d[28]), "=f"(d[29]), "=f"(d[30]), "=f"(d[31]), "=f"(d[32]), "=f"(d[33]), "=f"(d[34]), "=f"(d[35]), "=f"(d[36]), "=f"(d[37]), "=f"(d[38]), "=f"(d[39])
    : "r"(bq[0]), "r"(bq[1]), "r"(bq[2]), "r"(bq[3]), "r"(loSel)
    : "memory");
}
template<> __device__ __forceinline__ void g1_bias<11>(float* d, const uint32_t (&bq)[4], uint32_t loSel) {
  asm volatile("{\n.reg .b64 db;\n.reg .b32 zr;\n"
    "mov.b32 zr, 0;\nmov.b64 db, {%48, zr};\n"
    "wgmma.mma_async.sync.aligned.m64n88k16.f32.bf16.bf16 {%0, %1, %2, %3, %4, %5, %6, %7, %8, %9, %10, %11, %12, %13, %14, %15, %16, %17, %18, %19, %20, %21, %22, %23, %24, %25, %26, %27, %28, %29, %30, %31, %32, %33, %34, %35, %36, %37, %38, %39, %40, %41, %42, %43}, {%44, %45, %46, %47}, db, 0, 1, 1, 0;\n}\n"
    : "=f"(d[0]), "=f"(d[1]), "=f"(d[2]), "=f"(d[3]), "=f"(d[4]), "=f"(d[5]), "=f"(d[6]), "=f"(d[7]), "=f"(d[8]), "=f"(d[9]), "=f"(d[10]), "=f"(d[11]), "=f"(d[12]), "=f"(d[13]), "=f"(d[14]), "=f"(d[15]), "=f"(d[16]), "=f"(d[17]), "=f"(d[18]), "=f"(d[19]), "=f"(d[20]), "=f"(d[21]), "=f"(d[22]), "=f"(d[23]), "=f"(d[24]), "=f"(d[25]), "=f"(d[26]), "=f"(d[27]), "=f"(d[28]), "=f"(d[29]), "=f"(d[30]), "=f"(d[31]), "=f"(d[32]), "=f"(d[33]), "=f"(d[34]), "=f"(d[35]), "=f"(d[36]), "=f"(d[37]), "=f"(d[38]), "=f"(d[39]), "=f"(d[40]), "=f"(d[41]), "=f"(d[42]), "=f"(d[43])
    : "r"(bq[0]), "r"(bq[1]), "r"(bq[2]), "r"(bq[3]), "r"(loSel)
    : "memory");
}
template<> __device__ __forceinline__ void g1_bias<12>(float* d, const uint32_t (&bq)[4], uint32_t loSel) {
  asm volatile("{\n.reg .b64 db;\n.reg .b32 zr;\n"
    "mov.b32 zr, 0;\nmov.b64 db, {%52, zr};\n"
    "wgmma.mma_async.sync.aligned.m64n96k16.f32.bf16.bf16 {%0, %1, %2, %3, %4, %5, %6, %7, %8, %9, %10, %11, %12, %13, %14, %15, %16, %17, %18, %19, %20, %21, %22, %23, %24, %25, %26, %27, %28, %29, %30, %31, %32, %33, %34, %35, %36, %37, %38, %39, %40, %41, %42, %43, %44, %45, %46, %47}, {%48, %49, %50, %51}, db, 0, 1, 1, 0;\n}\n"
    : "=f"(d[0]), "=f"(d[1]), "=f"(d[2]), "=f"(d[3]), "=f"(d[4]), "=f"(d[5]), "=f"(d[6]), "=f"(d[7]), "=f"(d[8]), "=f"(d[9]), "=f"(d[10]), "=f"(d[11]), "=f"(d[12]), "=f"(d[13]), "=f"(d[14]), "=f"(d[15]), "=f"(d[16]), "=f"(d[17]), "=f"(d[18]), "=f"(d[19]), "=f"(d[20]), "=f"(d[21]), "=f"(d[22]), "=f"(d[23]), "=f"(d[24]), "=f"(d[25]), "=f"(d[26]), "=f"(d[27]), "=f"(d[28]), "=f"(d[29]), "=f"(d[30]), "=f"(d[31]), "=f"(d[32]), "=f"(d[33]), "=f"(d[34]), "=f"(d[35]), "=f"(d[36]), "=f"(d[37]), "=f"(d[38]), "=f"(d[39]), "=f"(d[40]), "=f"(d[41]), "=f"(d[42]), "=f"(d[43]), "=f"(d[44]), "=f"(d[45]), "=f"(d[46]), "=f"(d[47])
    : "r"(bq[0]), "r"(bq[1]), "r"(bq[2]), "r"(bq[3]), "r"(loSel)
    : "memory");
}
template<> __device__ __forceinline__ void g1_step<4>(float* d, const uint32_t* a, uint32_t loH, uint32_t hiH) {
  asm volatile("{\n.reg .b64 db;\nmov.b64 db, {%20, %21};\n"
    "wgmma.mma_async.sync.aligned.m64n32k16.f32.bf16.bf16 {%0, %1, %2, %3, %4, %5, %6, %7, %8, %9, %10, %11, %12, %13, %14, %15}, {%16, %17, %18, %19}, db, 1, 1, 1, 0;\n}\n"
    : "+f"(d[0]), "+f"(d[1]), "+f"(d[2]), "+f"(d[3]), "+f"(d[4]), "+f"(d[5]), "+f"(d[6]), "+f"(d[7]), "+f"(d[8]), "+f"(d[9]), "+f"(d[10]), "+f"(d[11]), "+f"(d[12]), "+f"(d[13]), "+f"(d[14]), "+f"(d[15])
    : "r"(a[0]), "r"(a[1]), "r"(a[2]), "r"(a[3]), "r"(loH), "r"(hiH)
    : "memory");
}
template<> __device__ __forceinline__ void g1_step<8>(float* d, const uint32_t* a, uint32_t loH, uint32_t hiH) {
  asm volatile("{\n.reg .b64 db;\nmov.b64 db, {%36, %37};\n"
    "wgmma.mma_async.sync.aligned.m64n64k16.f32.bf16.bf16 {%0, %1, %2, %3, %4, %5, %6, %7, %8, %9, %10, %11, %12, %13, %14, %15, %16, %17, %18, %19, %20, %21, %22, %23, %24, %25, %26, %27, %28, %29, %30, %31}, {%32, %33, %34, %35}, db, 1, 1, 1, 0;\n}\n"
    : "+f"(d[0]), "+f"(d[1]), "+f"(d[2]), "+f"(d[3]), "+f"(d[4]), "+f"(d[5]), "+f"(d[6]), "+f"(d[7]), "+f"(d[8]), "+f"(d[9]), "+f"(d[10]), "+f"(d[11]), "+f"(d[12]), "+f"(d[13]), "+f"(d[14]), "+f"(d[15]), "+f"(d[16]), "+f"(d[17]), "+f"(d[18]), "+f"(d[19]), "+f"(d[20]), "+f"(d[21]), "+f"(d[22]), "+f"(d[23]), "+f"(d[24]), "+f"(d[25]), "+f"(d[26]), "+f"(d[27]), "+f"(d[28]), "+f"(d[29]), "+f"(d[30]), "+f"(d[31])
    : "r"(a[0]), "r"(a[1]), "r"(a[2]), "r"(a[3]), "r"(loH), "r"(hiH)
    : "memory");
}
template<> __device__ __forceinline__ void g1_step<9>(float* d, const uint32_t* a, uint32_t loH, uint32_t hiH) {
  asm volatile("{\n.reg .b64 db;\nmov.b64 db, {%40, %41};\n"
    "wgmma.mma_async.sync.aligned.m64n72k16.f32.bf16.bf16 {%0, %1, %2, %3, %4, %5, %6, %7, %8, %9, %10, %11, %12, %13, %14, %15, %16, %17, %18, %19, %20, %21, %22, %23, %24, %25, %26, %27, %28, %29, %30, %31, %32, %33, %34, %35}, {%36, %37, %38, %39}, db, 1, 1, 1, 0;\n}\n"
    : "+f"(d[0]), "+f"(d[1]), "+f"(d[2]), "+f"(d[3]), "+f"(d[4]), "+f"(d[5]), "+f"(d[6]), "+f"(d[7]), "+f"(d[8]), "+f"(d[9]), "+f"(d[10]), "+f"(d[11]), "+f"(d[12]), "+f"(d[13]), "+f"(d[14]), "+f"(d[15]), "+f"(d[16]), "+f"(d[17]), "+f"(d[18]), "+f"(d[19]), "+f"(d[20]), "+f"(d[21]), "+f"(d[22]), "+f"(d[23]), "+f"(d[24]), "+f"(d[25]), "+f"(d[26]), "+f"(d[27]), "+f"(d[28]), "+f"(d[29]), "+f"(d[30]), "+f"(d[31]), "+f"(d[32]), "+f"(d[33]), "+f"(d[34]), "+f"(d[35])
    : "r"(a[0]), "r"(a[1]), "r"(a[2]), "r"(a[3]), "r"(loH), "r"(hiH)
    : "memory");
}
template<> __device__ __forceinline__ void g1_step<10>(float* d, const uint32_t* a, uint32_t loH, uint32_t hiH) {
  asm volatile("{\n.reg .b64 db;\nmov.b64 db, {%44, %45};\n"
    "wgmma.mma_async.sync.aligned.m64n80k16.f32.bf16.bf16 {%0, %1, %2, %3, %4, %5, %6, %7, %8, %9, %10, %11, %12, %13, %14, %15, %16, %17, %18, %19, %20, %21, %22, %23, %24, %25, %26, %27, %28, %29, %30, %31, %32, %33, %34, %35, %36, %37, %38, %39}, {%40, %41, %42, %43}, db, 1, 1, 1, 0;\n}\n"
    : "+f"(d[0]), "+f"(d[1]), "+f"(d[2]), "+f"(d[3]), "+f"(d[4]), "+f"(d[5]), "+f"(d[6]), "+f"(d[7]), "+f"(d[8]), "+f"(d[9]), "+f"(d[10]), "+f"(d[11]), "+f"(d[12]), "+f"(d[13]), "+f"(d[14]), "+f"(d[15]), "+f"(d[16]), "+f"(d[17]), "+f"(d[18]), "+f"(d[19]), "+f"(d[20]), "+f"(d[21]), "+f"(d[22]), "+f"(d[23]), "+f"(d[24]), "+f"(d[25]), "+f"(d[26]), "+f"(d[27]), "+f"(d[28]), "+f"(d[29]), "+f"(d[30]), "+f"(d[31]), "+f"(d[32]), "+f"(d[33]), "+f"(d[34]), "+f"(d[35]), "+f"(d[36]), "+f"(d[37]), "+f"(d[38]), "+f"(d[39])
    : "r"(a[0]), "r"(a[1]), "r"(a[2]), "r"(a[3]), "r"(loH), "r"(hiH)
    : "memory");
}
template<> __device__ __forceinline__ void g1_step<11>(float* d, const uint32_t* a, uint32_t loH, uint32_t hiH) {
  asm volatile("{\n.reg .b64 db;\nmov.b64 db, {%48, %49};\n"
    "wgmma.mma_async.sync.aligned.m64n88k16.f32.bf16.bf16 {%0, %1, %2, %3, %4, %5, %6, %7, %8, %9, %10, %11, %12, %13, %14, %15, %16, %17, %18, %19, %20, %21, %22, %23, %24, %25, %26, %27, %28, %29, %30, %31, %32, %33, %34, %35, %36, %37, %38, %39, %40, %41, %42, %43}, {%44, %45, %46, %47}, db, 1, 1, 1, 0;\n}\n"
    : "+f"(d[0]), "+f"(d[1]), "+f"(d[2]), "+f"(d[3]), "+f"(d[4]), "+f"(d[5]), "+f"(d[6]), "+f"(d[7]), "+f"(d[8]), "+f"(d[9]), "+f"(d[10]), "+f"(d[11]), "+f"(d[12]), "+f"(d[13]), "+f"(d[14]), "+f"(d[15]), "+f"(d[16]), "+f"(d[17]), "+f"(d[18]), "+f"(d[19]), "+f"(d[20]), "+f"(d[21]), "+f"(d[22]), "+f"(d[23]), "+f"(d[24]), "+f"(d[25]), "+f"(d[26]), "+f"(d[27]), "+f"(d[28]), "+f"(d[29]), "+f"(d[30]), "+f"(d[31]), "+f"(d[32]), "+f"(d[33]), "+f"(d[34]), "+f"(d[35]), "+f"(d[36]), "+f"(d[37]), "+f"(d[38]), "+f"(d[39]), "+f"(d[40]), "+f"(d[41]), "+f"(d[42]), "+f"(d[43])
    : "r"(a[0]), "r"(a[1]), "r"(a[2]), "r"(a[3]), "r"(loH), "r"(hiH)
    : "memory");
}
template<> __device__ __forceinline__ void g1_step<12>(float* d, const uint32_t* a, uint32_t loH, uint32_t hiH) {
  asm volatile("{\n.reg .b64 db;\nmov.b64 db, {%52, %53};\n"
    "wgmma.mma_async.sync.aligned.m64n96k16.f32.bf16.bf16 {%0, %1, %2, %3, %4, %5, %6, %7, %8, %9, %10, %11, %12, %13, %14, %15, %16, %17, %18, %19, %20, %21, %22, %23, %24, %25, %26, %27, %28, %29, %30, %31, %32, %33, %34, %35, %36, %37, %38, %39, %40, %41, %42, %43, %44, %45, %46, %47}, {%48, %49, %50, %51}, db, 1, 1, 1, 0;\n}\n"
    : "+f"(d[0]), "+f"(d[1]), "+f"(d[2]), "+f"(d[3]), "+f"(d[4]), "+f"(d[5]), "+f"(d[6]), "+f"(d[7]), "+f"(d[8]), "+f"(d[9]), "+f"(d[10]), "+f"(d[11]), "+f"(d[12]), "+f"(d[13]), "+f"(d[14]), "+f"(d[15]), "+f"(d[16]), "+f"(d[17]), "+f"(d[18]), "+f"(d[19]), "+f"(d[20]), "+f"(d[21]), "+f"(d[22]), "+f"(d[23]), "+f"(d[24]), "+f"(d[25]), "+f"(d[26]), "+f"(d[27]), "+f"(d[28]), "+f"(d[29]), "+f"(d[30]), "+f"(d[31]), "+f"(d[32]), "+f"(d[33]), "+f"(d[34]), "+f"(d[35]), "+f"(d[36]), "+f"(d[37]), "+f"(d[38]), "+f"(d[39]), "+f"(d[40]), "+f"(d[41]), "+f"(d[42]), "+f"(d[43]), "+f"(d[44]), "+f"(d[45]), "+f"(d[46]), "+f"(d[47])
    : "r"(a[0]), "r"(a[1]), "r"(a[2]), "r"(a[3]), "r"(loH), "r"(hiH)
    : "memory");
}
__device__ __forceinline__ void g2_first(float (&o)[16], const uint32_t* a, uint32_t loH, uint32_t meta, uint32_t hiH) {
  asm volatile("{\n.reg .b64 db;\nmov.b64 db, {%20, %22};\n"
    "wgmma.mma_async.sp.sync.aligned.m64n32k32.f32.bf16.bf16 {%0, %1, %2, %3, %4, %5, %6, %7, %8, %9, %10, %11, %12, %13, %14, %15}, {%16, %17, %18, %19}, db, %21, 0, 0, 1, 1, 1;\n}\n"
    : "=f"(o[0]), "=f"(o[1]), "=f"(o[2]), "=f"(o[3]), "=f"(o[4]), "=f"(o[5]), "=f"(o[6]), "=f"(o[7]), "=f"(o[8]), "=f"(o[9]), "=f"(o[10]), "=f"(o[11]), "=f"(o[12]), "=f"(o[13]), "=f"(o[14]), "=f"(o[15])
    : "r"(a[0]), "r"(a[1]), "r"(a[2]), "r"(a[3]), "r"(loH), "r"(meta), "r"(hiH)
    : "memory");
}
__device__ __forceinline__ void g2_more(float (&o)[16], const uint32_t* a, uint32_t loH, uint32_t meta, uint32_t hiH) {
  asm volatile("{\n.reg .b64 db;\nmov.b64 db, {%20, %22};\n"
    "wgmma.mma_async.sp.sync.aligned.m64n32k32.f32.bf16.bf16 {%0, %1, %2, %3, %4, %5, %6, %7, %8, %9, %10, %11, %12, %13, %14, %15}, {%16, %17, %18, %19}, db, %21, 0, 1, 1, 1, 1;\n}\n"
    : "+f"(o[0]), "+f"(o[1]), "+f"(o[2]), "+f"(o[3]), "+f"(o[4]), "+f"(o[5]), "+f"(o[6]), "+f"(o[7]), "+f"(o[8]), "+f"(o[9]), "+f"(o[10]), "+f"(o[11]), "+f"(o[12]), "+f"(o[13]), "+f"(o[14]), "+f"(o[15])
    : "r"(a[0]), "r"(a[1]), "r"(a[2]), "r"(a[3]), "r"(loH), "r"(meta), "r"(hiH)
    : "memory");
}
template<int N> __device__ __forceinline__ void mma_wait(float* d, Int<4>) {
  asm volatile("wgmma.wait_group.sync.aligned %16;"
    : "+f"(d[0]), "+f"(d[1]), "+f"(d[2]), "+f"(d[3]), "+f"(d[4]), "+f"(d[5]), "+f"(d[6]), "+f"(d[7]), "+f"(d[8]), "+f"(d[9]), "+f"(d[10]), "+f"(d[11]), "+f"(d[12]), "+f"(d[13]), "+f"(d[14]), "+f"(d[15])
    : "n"(N) : "memory");
}
template<int N> __device__ __forceinline__ void mma_wait(float* d, Int<8>) {
  asm volatile("wgmma.wait_group.sync.aligned %32;"
    : "+f"(d[0]), "+f"(d[1]), "+f"(d[2]), "+f"(d[3]), "+f"(d[4]), "+f"(d[5]), "+f"(d[6]), "+f"(d[7]), "+f"(d[8]), "+f"(d[9]), "+f"(d[10]), "+f"(d[11]), "+f"(d[12]), "+f"(d[13]), "+f"(d[14]), "+f"(d[15]), "+f"(d[16]), "+f"(d[17]), "+f"(d[18]), "+f"(d[19]), "+f"(d[20]), "+f"(d[21]), "+f"(d[22]), "+f"(d[23]), "+f"(d[24]), "+f"(d[25]), "+f"(d[26]), "+f"(d[27]), "+f"(d[28]), "+f"(d[29]), "+f"(d[30]), "+f"(d[31])
    : "n"(N) : "memory");
}
template<int N> __device__ __forceinline__ void mma_wait(float* d, Int<9>) {
  asm volatile("wgmma.wait_group.sync.aligned %36;"
    : "+f"(d[0]), "+f"(d[1]), "+f"(d[2]), "+f"(d[3]), "+f"(d[4]), "+f"(d[5]), "+f"(d[6]), "+f"(d[7]), "+f"(d[8]), "+f"(d[9]), "+f"(d[10]), "+f"(d[11]), "+f"(d[12]), "+f"(d[13]), "+f"(d[14]), "+f"(d[15]), "+f"(d[16]), "+f"(d[17]), "+f"(d[18]), "+f"(d[19]), "+f"(d[20]), "+f"(d[21]), "+f"(d[22]), "+f"(d[23]), "+f"(d[24]), "+f"(d[25]), "+f"(d[26]), "+f"(d[27]), "+f"(d[28]), "+f"(d[29]), "+f"(d[30]), "+f"(d[31]), "+f"(d[32]), "+f"(d[33]), "+f"(d[34]), "+f"(d[35])
    : "n"(N) : "memory");
}
template<int N> __device__ __forceinline__ void mma_wait(float* d, Int<10>) {
  asm volatile("wgmma.wait_group.sync.aligned %40;"
    : "+f"(d[0]), "+f"(d[1]), "+f"(d[2]), "+f"(d[3]), "+f"(d[4]), "+f"(d[5]), "+f"(d[6]), "+f"(d[7]), "+f"(d[8]), "+f"(d[9]), "+f"(d[10]), "+f"(d[11]), "+f"(d[12]), "+f"(d[13]), "+f"(d[14]), "+f"(d[15]), "+f"(d[16]), "+f"(d[17]), "+f"(d[18]), "+f"(d[19]), "+f"(d[20]), "+f"(d[21]), "+f"(d[22]), "+f"(d[23]), "+f"(d[24]), "+f"(d[25]), "+f"(d[26]), "+f"(d[27]), "+f"(d[28]), "+f"(d[29]), "+f"(d[30]), "+f"(d[31]), "+f"(d[32]), "+f"(d[33]), "+f"(d[34]), "+f"(d[35]), "+f"(d[36]), "+f"(d[37]), "+f"(d[38]), "+f"(d[39])
    : "n"(N) : "memory");
}
template<int N> __device__ __forceinline__ void mma_wait(float* d, Int<11>) {
  asm volatile("wgmma.wait_group.sync.aligned %44;"
    : "+f"(d[0]), "+f"(d[1]), "+f"(d[2]), "+f"(d[3]), "+f"(d[4]), "+f"(d[5]), "+f"(d[6]), "+f"(d[7]), "+f"(d[8]), "+f"(d[9]), "+f"(d[10]), "+f"(d[11]), "+f"(d[12]), "+f"(d[13]), "+f"(d[14]), "+f"(d[15]), "+f"(d[16]), "+f"(d[17]), "+f"(d[18]), "+f"(d[19]), "+f"(d[20]), "+f"(d[21]), "+f"(d[22]), "+f"(d[23]), "+f"(d[24]), "+f"(d[25]), "+f"(d[26]), "+f"(d[27]), "+f"(d[28]), "+f"(d[29]), "+f"(d[30]), "+f"(d[31]), "+f"(d[32]), "+f"(d[33]), "+f"(d[34]), "+f"(d[35]), "+f"(d[36]), "+f"(d[37]), "+f"(d[38]), "+f"(d[39]), "+f"(d[40]), "+f"(d[41]), "+f"(d[42]), "+f"(d[43])
    : "n"(N) : "memory");
}
template<int N> __device__ __forceinline__ void mma_wait(float* d, Int<12>) {
  asm volatile("wgmma.wait_group.sync.aligned %48;"
    : "+f"(d[0]), "+f"(d[1]), "+f"(d[2]), "+f"(d[3]), "+f"(d[4]), "+f"(d[5]), "+f"(d[6]), "+f"(d[7]), "+f"(d[8]), "+f"(d[9]), "+f"(d[10]), "+f"(d[11]), "+f"(d[12]), "+f"(d[13]), "+f"(d[14]), "+f"(d[15]), "+f"(d[16]), "+f"(d[17]), "+f"(d[18]), "+f"(d[19]), "+f"(d[20]), "+f"(d[21]), "+f"(d[22]), "+f"(d[23]), "+f"(d[24]), "+f"(d[25]), "+f"(d[26]), "+f"(d[27]), "+f"(d[28]), "+f"(d[29]), "+f"(d[30]), "+f"(d[31]), "+f"(d[32]), "+f"(d[33]), "+f"(d[34]), "+f"(d[35]), "+f"(d[36]), "+f"(d[37]), "+f"(d[38]), "+f"(d[39]), "+f"(d[40]), "+f"(d[41]), "+f"(d[42]), "+f"(d[43]), "+f"(d[44]), "+f"(d[45]), "+f"(d[46]), "+f"(d[47])
    : "n"(N) : "memory");
}

__device__ __forceinline__ uint32_t smem_u32(const void* p) { return (uint32_t)__cvta_generic_to_shared(p); }

__device__ __forceinline__ void mbar_init(uint32_t bar, uint32_t cnt) {
  asm volatile("mbarrier.init.shared::cta.b64 [%0], %1;" :: "r"(bar), "r"(cnt) : "memory");
}
__device__ __forceinline__ void mbar_arrive(uint32_t bar) {
  asm volatile("mbarrier.arrive.shared::cta.b64 _, [%0];" :: "r"(bar) : "memory");
}
__device__ __forceinline__ void mbar_wait(uint32_t bar, uint32_t parity) {
  asm volatile("{\n.reg .pred p;\n.reg .u32 n;\n"
               "mov.u32 n, 0;\n"
               "WAIT_LOOP:\n"
               "mbarrier.try_wait.parity.shared::cta.b64 p, [%0], %1;\n"
               "@p bra.uni WAIT_DONE;\n"
               "add.u32 n, n, 1;\n"
               "setp.lt.u32 p, n, 0x1000000;\n"
               "@p bra.uni WAIT_LOOP;\n"
               "trap;\n"
               "WAIT_DONE:\n}\n"
               :: "r"(bar), "r"(parity) : "memory");
}
__device__ __forceinline__ uint32_t mbar_test(uint32_t bar, uint32_t parity) {
  uint32_t ok;
  asm volatile("{\n.reg .pred p;\nmbarrier.test_wait.parity.shared::cta.b64 p, [%1], %2;\nselp.u32 %0, 1, 0, p;\n}\n"
               : "=r"(ok) : "r"(bar), "r"(parity) : "memory");
  return ok;
}
__device__ __forceinline__ void cp_async16(uint32_t dst, const void* src) {
  asm volatile("cp.async.cg.shared.global [%0], [%1], 16;" :: "r"(dst), "l"(src) : "memory");
}
template<int T, int I, bool Z>
__device__ __forceinline__ void cp_row(uint32_t dst, uint64_t& a, uint32_t rows4, uint32_t base, int left, uint64_t pol) {
#define DIN_ADDR "mov.b64 {x, y}, %0;\ndp4a.u32.u32 x, %2, %8, %5;\nmov.b64 %0, {x, y};\n"
  if (Z)
    asm volatile("{\n.reg .u32 x, y;\n.reg .pred p;\n" DIN_ADDR "setp.le.s32 p, %6, %7;\n"
                 "cp.async.cg.shared.global.L2::cache_hint [%1 + %4], [%0], 16, p, %3;\n}\n"
                 : "+l"(a) : "r"(dst), "r"(rows4), "l"(pol), "n"(T * 2048), "r"(base), "r"(left), "n"(T * 16 + I), "n"(0x80u << 8 * I) : "memory");
  else
    asm volatile("{\n.reg .u32 x, y;\n" DIN_ADDR
                 "cp.async.cg.shared.global.L2::cache_hint [%1 + %4], [%0], 16, %3;\n}\n"
                 : "+l"(a) : "r"(dst), "r"(rows4), "l"(pol), "n"(T * 2048), "r"(base), "r"(left), "n"(T * 16 + I), "n"(0x80u << 8 * I) : "memory");
}
template<int T, bool Z>
__device__ __forceinline__ void cp_group(const uint32_t (&dst)[4], uint64_t& a, uint32_t rows4, uint32_t base, int left, uint64_t pol) {
  cp_row<T, 0, Z>(dst[0], a, rows4, base, left, pol);
  cp_row<T, 1, Z>(dst[1], a, rows4, base, left, pol);
  cp_row<T, 2, Z>(dst[2], a, rows4, base, left, pol);
  cp_row<T, 3, Z>(dst[3], a, rows4, base, left, pol);
}
__device__ __forceinline__ uint32_t prmt(uint32_t a, uint32_t b, uint32_t sel) {
  uint32_t d;
  asm("prmt.b32 %0, %1, %2, %3;" : "=r"(d) : "r"(a), "r"(b), "r"(sel));
  return d;
}
__device__ __forceinline__ uint32_t ballot_bit(uint32_t x, uint32_t bit) {
  uint32_t d;
  asm volatile("{\n.reg .pred p;\n.reg .u32 t;\nand.b32 t, %1, %2;\nsetp.ne.u32 p, t, 0;\nvote.sync.ballot.b32 %0, p, 0xffffffff;\n}\n"
               : "=r"(d) : "r"(x), "r"(bit));
  return d;
}
__device__ __forceinline__ uint4 load_mask(const void* mask, uint32_t b, uint32_t i) {
  uint4 m;
  asm volatile("ld.global.nc.L1::no_allocate.v4.u32 {%0,%1,%2,%3}, [%4];"
               : "=r"(m.x), "=r"(m.y), "=r"(m.z), "=r"(m.w) : "l"(reinterpret_cast<const uint4*>(mask) + (b * 25u + i)));
  return m;
}
__device__ __forceinline__ uint32_t nonzero_as_one(uint32_t x) {
  uint32_t d;
  asm("set.neu.bf16x2.bf16x2 %0, %1, %2;" : "=r"(d) : "r"(x), "r"(0u));
  return d;
}
__device__ __forceinline__ void cp_async_arrive_noinc(uint32_t bar) {
  asm volatile("cp.async.mbarrier.arrive.noinc.shared::cta.b64 [%0];" :: "r"(bar) : "memory");
}
__device__ __forceinline__ void ldsm_x4(uint32_t addr, uint32_t& r0, uint32_t& r1, uint32_t& r2, uint32_t& r3) {
  asm volatile("ldmatrix.sync.aligned.m8n8.x4.shared.b16 {%0,%1,%2,%3}, [%4];"
               : "=r"(r0), "=r"(r1), "=r"(r2), "=r"(r3) : "r"(addr) : "memory");
}
__device__ __forceinline__ void ldsm_x4_t(uint32_t addr, uint32_t& r0, uint32_t& r1, uint32_t& r2, uint32_t& r3) {
  asm volatile("ldmatrix.sync.aligned.m8n8.x4.trans.shared.b16 {%0,%1,%2,%3}, [%4];"
               : "=r"(r0), "=r"(r1), "=r"(r2), "=r"(r3) : "r"(addr) : "memory");
}
__device__ __forceinline__ void stsm_x4_t(uint32_t addr, uint32_t r0, uint32_t r1, uint32_t r2, uint32_t r3) {
  asm volatile("stmatrix.sync.aligned.m8n8.x4.trans.shared.b16 [%0], {%1,%2,%3,%4};"
               :: "r"(addr), "r"(r0), "r"(r1), "r"(r2), "r"(r3) : "memory");
}
__device__ __forceinline__ uint32_t hfma2_bf16(uint32_t a, uint32_t b, uint32_t c) {
  uint32_t d;
  asm volatile("fma.rn.bf16x2 %0, %1, %2, %3;" : "=r"(d) : "r"(a), "r"(b), "r"(c));
  return d;
}
__device__ __forceinline__ uint32_t pack_bf16(float lo, float hi) {
  uint32_t d;
  asm("cvt.rn.bf16x2.f32 %0, %1, %2;" : "=r"(d) : "f"(hi), "f"(lo));
  return d;
}
__device__ __forceinline__ uint32_t lds32(uint32_t a) {
  uint32_t v; asm volatile("ld.shared.u32 %0, [%1];" : "=r"(v) : "r"(a) : "memory"); return v;
}
__device__ __forceinline__ uint32_t lds16(uint32_t a) {
  uint32_t v; asm volatile("ld.shared.u16 %0, [%1];" : "=r"(v) : "r"(a) : "memory"); return v;
}
__device__ __forceinline__ void sts32(uint32_t a, uint32_t v) {
  asm volatile("st.shared.u32 [%0], %1;" :: "r"(a), "r"(v) : "memory");
}
__device__ __forceinline__ void sts16(uint32_t a, uint32_t v) {
  asm volatile("st.shared.u16 [%0], %1;" :: "r"(a), "h"((unsigned short)v) : "memory");
}
__device__ __forceinline__ void sts8(uint32_t a, uint32_t v) {
  asm volatile("st.shared.u8 [%0], %1;" :: "r"(a), "r"(v) : "memory");
}
constexpr uint32_t DESC_ROWS = 0x40000040u, DESC_HALVES = 0x80000020u;
__device__ __forceinline__ uint32_t desc_lo(uint32_t addr) { return ((addr & 0x3FFFF) >> 4) | (1u << 16); }

__device__ __forceinline__ uint4 lds128(uint32_t a) {
  uint4 v;
  asm volatile("ld.shared.v4.u32 {%0,%1,%2,%3}, [%4];" : "=r"(v.x), "=r"(v.y), "=r"(v.z), "=r"(v.w) : "r"(a) : "memory");
  return v;
}
__device__ __forceinline__ void sts128(uint32_t a, uint4 v) {
  asm volatile("st.shared.v4.u32 [%0], {%1,%2,%3,%4};" :: "r"(a), "r"(v.x), "r"(v.y), "r"(v.z), "r"(v.w) : "memory");
}
__device__ __forceinline__ void prefetch_l2(const void* p, uint32_t bytes) {
  asm volatile("cp.async.bulk.prefetch.L2.global [%0], %1;" :: "l"(p), "r"(bytes) : "memory");
}

__device__ __forceinline__ void cut_here(uint32_t& any, uint32_t zero) {
  asm volatile("{\n.reg .pred p;\nsetp.ne.u32 p, %1, 0;\n@p mov.u32 %0, %%clock;\n}\n" : "+r"(any) : "r"(zero) : "memory");
}
__device__ __forceinline__ void mma_fence() { asm volatile("wgmma.fence.sync.aligned;" ::: "memory"); }
__device__ __forceinline__ void mma_commit() { asm volatile("wgmma.commit_group.sync.aligned;" ::: "memory"); }
template<bool FIRST>
__device__ __forceinline__ void hmma(float (&c)[4], const uint32_t* a, uint32_t b0, uint32_t b1) {
  if (FIRST)
    asm volatile("mma.sync.aligned.m16n8k16.row.col.f32.bf16.bf16.f32 {%0,%1,%2,%3}, {%4,%5,%6,%7}, {%8,%9}, {%10,%10,%10,%10};"
                 : "=f"(c[0]), "=f"(c[1]), "=f"(c[2]), "=f"(c[3]) : "r"(a[0]), "r"(a[1]), "r"(a[2]), "r"(a[3]), "r"(b0), "r"(b1), "f"(0.f));
  else
    asm volatile("mma.sync.aligned.m16n8k16.row.col.f32.bf16.bf16.f32 {%0,%1,%2,%3}, {%4,%5,%6,%7}, {%8,%9}, {%0,%1,%2,%3};"
                 : "+f"(c[0]), "+f"(c[1]), "+f"(c[2]), "+f"(c[3]) : "r"(a[0]), "r"(a[1]), "r"(a[2]), "r"(a[3]), "r"(b0), "r"(b1));
}
__device__ __forceinline__ void tanh_some(float* d, int i0, int i1) {
#pragma unroll
  for (int i = i0; i < i1; i++) asm volatile("tanh.approx.f32 %0, %0;" : "+f"(d[i ^ 2]));
}
__device__ __forceinline__ uint32_t mix(const float* d, int i, float r) {
  uint32_t p;
  asm volatile("{\n.reg .f32 x, y;\nfma.rn.f32 x, %3, %5, %1;\nfma.rn.f32 y, %4, %5, %2;\ncvt.rn.bf16x2.f32 %0, y, x;\n}\n"
               : "=r"(p) : "f"(d[4 * i]), "f"(d[4 * i + 1]), "f"(d[4 * i + 2]), "f"(d[4 * i + 3]), "f"(r));
  return p;
}
__device__ __forceinline__ uint32_t sums_at(uint32_t d) { return S_OUT + (d ^ ((d >> 3) & 1)) * 16; }
template<int K> __device__ __forceinline__ uint32_t keep(uint32_t x) { return K ? __shfl_sync(0xffffffffu, x, 0) : x; }

__global__ void __launch_bounds__(NTHREADS, 1)
din_kernel(const __nv_bfloat16* __restrict__ mask, const __nv_bfloat16* __restrict__ target, int B, int grid,
           uint32_t pf_mask, uint32_t pf_tgt, const __nv_bfloat16* __restrict__ w1, const __nv_bfloat16* __restrict__ hist,
           const __nv_bfloat16* __restrict__ b1, const __nv_bfloat16* __restrict__ w2,
           const __nv_bfloat16* __restrict__ b2, __nv_bfloat16* __restrict__ out, unsigned int* counter, int pace16,
           int slow_pace, int slow_from) {
  {
    const char* pm = reinterpret_cast<const char*>(mask) + (size_t)blockIdx.x * pf_mask;
    const char* pt = reinterpret_cast<const char*>(target) + (size_t)blockIdx.x * pf_tgt;
    const uint32_t o = threadIdx.x * 128;
    asm volatile("{\n.reg .pred p;\nsetp.lt.u32 p, %1, %2;\n@p prefetch.global.L2 [%0];\n}\n" :: "l"(pm + o), "r"(o), "r"(pf_mask));
    asm volatile("{\n.reg .pred p;\nsetp.lt.u32 p, %1, %2;\n@p prefetch.global.L2 [%0];\n}\n" :: "l"(pt + o), "r"(o), "r"(pf_tgt));
  }
  extern __shared__ unsigned char smem_raw[];
  const uint32_t sb = (smem_u32(smem_raw) + 1023u) & ~1023u;
  const int tid = threadIdx.x, lane = tid & 31;
  const int warp = __shfl_sync(0xffffffffu, tid >> 5, 0);
#define ACT NCW
  const int bstep = ACT * grid;

  if (warp < NCW * 4) {
    const int wg = warp >> 2, w = warp & 3;
    const int g = lane >> 2;
    const uint32_t ring = sb + wg * RING_BYTES;
    const bool active = wg * grid + (int)blockIdx.x < B && wg < ACT;
    {
      const int t = tid & 127;
      const uint32_t dst = sb + ((t ^ ((t >> 3) & 7)) << 4);
      const char* src = reinterpret_cast<const char*>(w1) + t * 16;
#pragma unroll
      for (int i = 0; i < 4; i++) cp_async16(dst + w1_at(i) + wg * 2048, src + i * 8192 + wg * 2048);
      cp_async16(dst + w1_at(0) + wg * 8192 + 6144, src + wg * 8192 + 6144);
      if (wg == 0) cp_async16(dst + w1_at(3) + 6144, src + 3 * 8192 + 6144);
      if (lane < 8) {
        if (w == 0 && active) cp_async16(ring + R_TGT0 + lane * 16, target + (size_t)(wg * grid + blockIdx.x) * kD + lane * 8);
        if (w == 1 && wg < 2) cp_async16(ring + R_VEC + lane * 16, (wg ? w2 : b1) + lane * 8);
      }
    }
    if (w == 2) sts32(ring + R_SEL + lane * 4, 0x3e803e80u);
    uint32_t rb2;
    asm volatile("ld.global.nc.u16 %0, [%1];" : "=r"(rb2) : "l"(b2));
    asm volatile("setmaxnreg.inc.sync.aligned.u32 %0;" :: "n"(CONS_REGS));
    asm volatile("cp.async.wait_all;" ::: "memory");
    asm volatile("bar.sync 1, %0;" :: "n"(NCW * 160) : "memory");
    float r;
    uint32_t cq, swap, half2, bf[4];
    {
      const uint32_t v2 = sb + RING_BYTES + R_VEC + ((lane & 24) * 2 + (lane & 7)) * 2;
      const float x = __uint_as_float(lds16(v2) << 16), y = __uint_as_float(lds16(v2 + 16) << 16);
      float c = x + y;
#pragma unroll
      for (int o = 16; o; o >>= 1) c += __shfl_xor_sync(0xffffffffu, c, o);
      c = 0.5f * c + __uint_as_float(rb2 << 16);
      const bool sw = fabsf(y) > fabsf(x);
      const float u = sw ? y : x, v = sw ? x : y;
      const bool off = !(fabsf(u) > fabsf(c) * 0x1p-40f);
      const float sc = off ? __uint_as_float(max(__float_as_uint(c) & 0x7f800000u, 8u << 23) - (4u << 23)) : 0.5f * u;
      float upto = fabsf(sc);
#pragma unroll
      for (int o = 2; o < 32; o *= 2) {
        const float z = __shfl_up_sync(0xffffffffu, upto, o);
        if (lane >= o) upto += z;
      }
      const float all = __shfl_sync(0xffffffffu, upto, 30 + (lane & 1));
      const float m = c / all;
      const float grid_ = __uint_as_float((__float_as_uint(2.0625f + 1.03125f * fabsf(m)) & 0x7f800000u) - (7u << 23));
      const float m0 = __fadd_rn(__fadd_rn(m, grid_ * 0x1.8p23f), grid_ * -0x1.8p23f);
      const float rest = fmaf(-m0, all, c);
      float q = (upto - 0.5f * fabsf(sc)) * grid_ < fabsf(rest) ? m0 + copysignf(grid_, rest) : m0;
      if (sc < 0.f) q = -q;
      const int own = 8 * w + g;
      r = __shfl_sync(0xffffffffu, off ? 0.f : v / u, own);
      cq = __shfl_sync(0xffffffffu, pack_bf16(q, q), own);
      swap = __shfl_sync(0xffffffffu, sw, own);
      half2 = __shfl_sync(0xffffffffu, off ? 0u : 0x3f003f00u, own);
      const int odd = (g ^ (g >> 1)) & 1;
#pragma unroll
      for (int i = 0; i < 4; i++)
        bf[i] = (__float_as_uint(__shfl_sync(0xffffffffu, sc, 8 * i + 2 * (lane & 3) + odd)) >> 16) << (16 * odd);
      if (warp == 0) {
        sts128(sb + SCALES + lane * 16, make_uint4(bf[0], bf[1], bf[2], bf[3]));
        asm volatile("bar.arrive 6, 160;" ::: "memory");
      }
    }
    const uint32_t nhalf2 = half2 ^ 0x80008000u, nzero2 = 0x80008000u;
    const uint32_t vec = sb + R_VEC + (16 * w + g) * 2;
    const float b1a = __uint_as_float(half2 << 16) * __uint_as_float(lds16(vec + (swap ? 16 : 0)) << 16);
    const float b1b = __uint_as_float(half2 << 16) * __uint_as_float(lds16(vec + (swap ? 0 : 16)) << 16);
    uint32_t wac[16], wd[16], wbc[16];
    {
      const int mi = lane >> 3, rr = lane & 7;
      const uint32_t a0 = sb + (8 * (mi >> 1) + rr) * 128 + (((2 * w + (mi & 1)) ^ rr) << 4);
#pragma unroll
      for (int ks = 0; ks < 4; ks++) {
        uint32_t A[4], Bm[4], C[4], Dm[4];
        ldsm_x4_t(a0 + ks * 2048 + w1_at(0), A[0], A[1], A[2], A[3]);
        ldsm_x4_t(a0 + ks * 2048 + w1_at(1), Bm[0], Bm[1], Bm[2], Bm[3]);
        ldsm_x4_t(a0 + ks * 2048 + w1_at(2), C[0], C[1], C[2], C[3]);
        ldsm_x4_t(a0 + ks * 2048 + w1_at(3), Dm[0], Dm[1], Dm[2], Dm[3]);
#pragma unroll
        for (int e = 0; e < 4; e++) {
          A[e] = hfma2_bf16(A[e], half2, hfma2_bf16(C[e], half2, nzero2));
          Bm[e] = hfma2_bf16(Bm[e], half2, hfma2_bf16(C[e], nhalf2, nzero2));
          Dm[e] = hfma2_bf16(Dm[e], half2, nzero2);
        }
#pragma unroll
        for (int e = 0; e < 4; e++) {
          wac[4 * ks + e] = swap ? A[e ^ 1] : A[e];
          wbc[4 * ks + e] = swap ? Bm[e ^ 1] : Bm[e];
          wd[4 * ks + e] = swap ? Dm[e ^ 1] : Dm[e];
        }
      }
    }
    asm volatile("fence.proxy.async.shared::cta;" ::: "memory");
    asm volatile("bar.sync 5, %0;" :: "n"(NCW * 128) : "memory");

    const uint32_t ln = __shfl_sync(0xffffffffu, lane, lane);
    const uint32_t meta = __shfl_sync(0xffffffffu, g & 1 ? 0xdd8888ddu : 0x88dddd88u, lane);
    const uint32_t zr = grid >> 20;
    const uint32_t sel = keep<K_SEL>(((ring + R_SEL) & 0x3FFFF) >> 4);
    const uint32_t rat = __shfl_sync(0xffffffffu, sums_at(8 * w + (lane & 7)) + (lane >> 3) * 512, lane);
    const uint32_t barid = __shfl_sync(0xffffffffu, 2 + (tid >> 7), lane);
    const uint32_t toff = __shfl_sync(0xffffffffu, (lane & 24) << 1, lane);
    const uint32_t ost = __shfl_sync(0xffffffffu, w * 1024 + sums_at(lane), lane);
    if (active) {
      uint32_t t[8];
      auto load_t = [&](uint32_t ta) {
        ldsm_x4(ta + toff, t[0], t[1], t[2], t[3]);
        ldsm_x4(ta + toff + 64, t[4], t[5], t[6], t[7]);
      };
      load_t(ring + R_TGT0);
      uint32_t hdr = keep<1>(ring), raw, cur = hdr + (R_START - S_EMPTY);
      uint32_t x, nxt;
      auto peek_header = [&]() {
        nxt = hdr & H_NEXT;
        if (K_NX) asm volatile("" : "+r"(nxt));
        x = lds32(nxt + S_HDR);
      };
      auto next_header = [&]() {
        asm volatile("{\n.reg .pred p;\n.reg .u32 n;\n.reg .s32 y;\n"
                     "xor.b32 y, %0, %2;\nsetp.ge.s32 p, y, 0;\n@p bra.uni FRESH;\n"
                     "mov.u32 n, 0;\n"
                     "AGAIN:\nadd.u32 n, n, 1;\nsetp.gt.u32 p, n, 0x1000000;\n@p trap;\nnanosleep.u32 32;\n"
                     "ld.shared.u32 %0, [%1];\nxor.b32 y, %0, %2;\nsetp.lt.s32 p, y, 0;\n@p bra.uni AGAIN;\n"
                     "FRESH:\n}\n" : "+r"(x) : "r"(nxt + S_HDR), "r"(hdr << 1) : "memory");
        if (!K_TOP) raw = __shfl_sync(0xffffffffu, x, 0);
      };
      peek_header();
      next_header();
      while (true) {
        __syncwarp();
        if (ln == 0) mbar_arrive(cur + S_EMPTY);
        cur = nxt;
        hdr = K_TOP ? __shfl_sync(0xffffffffu, x, 0) : raw;
        uint32_t we[16], bq[4];
        {
          float c[4][4];
          asm volatile("mma.sync.aligned.m16n8k16.row.col.f32.bf16.bf16.f32 {%0,%1,%2,%3}, {%4,%5,%6,%7}, {%8,%9}, {%10,%11,%12,%13};"
                       : "=f"(c[0][0]), "=f"(c[0][1]), "=f"(c[0][2]), "=f"(c[0][3])
                       : "r"(wbc[0]), "r"(wbc[1]), "r"(wbc[2]), "r"(wbc[3]), "r"(t[0]), "r"(t[1]), "f"(b1a), "f"(r), "f"(b1b), "f"(__uint_as_float(cq)));
#pragma unroll
          for (int i = 1; i < 4; i++) hmma<true>(c[i], wbc + 4 * i, t[2 * i], t[2 * i + 1]);
#pragma unroll
          for (int i = 0; i < 16; i++) we[i] = hfma2_bf16(t[i >> 1], wd[i], wac[i]);
#pragma unroll
          for (int i = 0; i < 4; i++) bq[i] = pack_bf16(c[i & 2][2 * (i & 1)], c[(i & 2) + 1][2 * (i & 1)]);
        }
        auto chunk = [&](auto groups) {
          constexpr int N8 = decltype(groups)::value, KE = (N8 + 1) / 2, KA = KE - KL;
          float d[4 * N8], o[16];
          uint32_t a[4 * KE];
          auto scores = [&](int i0, int i1) {
#pragma unroll
            for (int i = i0; i < i1; i++) {
              a[2 * i] = i < N8 ? mix(d, i, r) : 0;
              a[2 * i + 1] = i < N8 ? hfma2_bf16(a[2 * i], 0x3f803f80u, cq) : 0;
              if (N8 == 16) {
                uint32_t m = 0x3f803f80u;
                asm volatile("{\n.reg .pred p;\nsetp.ne.u32 p, %1, 0;\n@p ld.shared.u32 %0, [%2];\n}\n"
                             : "+r"(m) : "r"(hdr & H_GENERAL), "r"(cur + S_MASK + i * 16 + (ln & 3) * 4) : "memory");
                a[2 * i] = hfma2_bf16(a[2 * i], m, 0x80008000u);
                a[2 * i + 1] = hfma2_bf16(a[2 * i + 1], m, 0x80008000u);
              }
            }
          };
          const uint32_t lo = cur >> 4, lo1 = lo + 0x10000, lo2 = lo + K_LO2 * 0x10000;
          const uint32_t hi1 = DESC_ROWS + (K_HI1 == 1 ? cur >> 24 : lo >> 19);
          const uint32_t hi2 = K_HI2 == 1 ? DESC_HALVES + (cur >> 24) : hi1 + (DESC_HALVES - DESC_ROWS);
          auto g2 = [&](int k) {
            if (k == 0) g2_first(o, a, lo2, meta, hi2); else g2_more(o, a + 4 * k, lo2 + 128 * k, meta, hi2);
          };
          uint32_t oa = cur + ost;
          mma_fence();
          g1_bias<NA>(d, bq, sel);
          g1_bias<N8 - NA>(d + 4 * NA, bq, sel);
          mma_commit();
          mbar_wait(cur + S_FULL, hdr >> 31);
          mma_fence();
#pragma unroll
          for (int k = 0; k < 4; k++) g1_step<NA>(d, we + 4 * k, lo1 + 2 * k, hi1);
          mma_commit();
#pragma unroll
          for (int k = 0; k < 4; k++) g1_step<N8 - NA>(d + 4 * NA, we + 4 * k, lo1 + 64 * NA + 2 * k, hi1);
          mma_commit();
          mma_wait<1>(d, Int<NA>());
          tanh_some(d, 0, 4 * NA);
          scores(0, S0);
          cut_here(oa, zr);
          mma_wait<0>(d + 4 * NA, Int<N8 - NA>());
          load_t(cur + S_TGT);
          peek_header();
          tanh_some(d, 4 * NA, 8 * KA + D0);
          scores(S0, 2 * KA);
          mma_fence();
#pragma unroll
          for (int k = 0; k < KA; k++) {
            g2(k);
            if (k == KA - KC) cut_here(oa, zr);
          }
          mma_commit();
          tanh_some(d, 8 * KA + D0, 4 * N8);
          scores(2 * KA, 2 * KE);
          mma_fence();
#pragma unroll
          for (int k = KA; k < KE; k++) g2(k);
          mma_commit();
          next_header();
          mma_wait<0>(o, Int<4>());
#pragma unroll
          for (int e = 0; e < 2; e++)
            stsm_x4_t(oa + e * 512, pack_bf16(o[2 * e], o[2 * e + 1]), pack_bf16(o[2 * e + 4], o[2 * e + 5]),
                      pack_bf16(o[2 * e + 8], o[2 * e + 9]), pack_bf16(o[2 * e + 12], o[2 * e + 13]));
        };
        if (hdr & H_13) { chunk(Int<13>()); if (hdr & (H_FINAL | H_12)) break; }
        else if (hdr & H_12) { chunk(Int<12>()); if (hdr & (H_FINAL | H_14)) break; }
        else if (hdr & H_14) { chunk(Int<14>()); if (hdr & (H_FINAL | H_15)) break; }
        else if (hdr & H_15) { chunk(Int<15>()); if (hdr & (H_FINAL | H_16)) break; }
        else { chunk(Int<16>()); if (hdr & H_FINAL) break; }
      }
      asm volatile("bar.sync %0, 128;" :: "r"(K_BAR ? barid : 2 + wg) : "memory");
      uint32_t u[8], l2 = ln;
      ldsm_x4(cur + rat, u[0], u[1], u[2], u[3]);
      ldsm_x4(cur + rat + 2048, u[4], u[5], u[6], u[7]);
      cut_here(l2, zr);
      __nv_bfloat16* dst = out + (x * kD + 8 * w + (l2 >> 2) + (l2 & 1) * 32);
      uint32_t skip = (l2 & 2) | (~hdr & H_SELF);
      asm volatile("" : "+l"(dst));
      cut_here(skip, zr);
      float c[4], e[4];
      hmma<true>(c, u, bf[0], bf[1]);
      hmma<true>(e, u + 4, bf[2], bf[3]);
      asm volatile("{\n.reg .pred p;\nsetp.eq.u32 p, %2, 0;\n@p st.global.u16 [%0], %1;\n}\n"
                   :: "l"(dst), "h"(__bfloat16_as_ushort(__float2bfloat16((c[0] + c[3]) + (e[0] + e[3])))), "r"(skip) : "memory");
      if (!(hdr & H_SELF) && ln == 0) mbar_arrive(cur + S_EMPTY);
    }
  } else {
    const int pw = warp - NCW * 4;
    const uint32_t ring = sb + pw * RING_BYTES;
    asm volatile("setmaxnreg.dec.sync.aligned.u32 %0;" :: "n"(PROD_REGS));
    if (pw < NCW) {
      int b = pw * grid + blockIdx.x, bn = b + bstep;
      uint4 mw = load_mask(mask, min(b, B - 1), min(lane, 24));
      if (lane == 0) {
#pragma unroll
        for (int i = 0; i < NSLOT; i++) {
          mbar_init(ring + i * SLOT_BYTES + S_FULL, 34);
          mbar_init(ring + i * SLOT_BYTES + S_EMPTY, 4);
          mbar_arrive(ring + i * SLOT_BYTES + S_FULL);
          sts32(ring + i * SLOT_BYTES + S_HDR, 0x80000000u);
        }
        mbar_init(ring + R_START, 4);
        sts32(ring + R_STOP, pw < ACT ? 0 : ring);
      }
      sts32(sb + R_PACE + lane * 4, 0);
      asm volatile("bar.arrive 1, %0;" :: "n"(NCW * 160) : "memory");
      asm volatile("bar.arrive 6, 160;" ::: "memory");
      if (pw >= ACT) return;
      const uint32_t list = ring + R_LIST;
      uint32_t lt;
      asm("mov.u32 %0, %%lanemask_lt;" : "=r"(lt));
      const uint32_t ln = __shfl_sync(0xffffffffu, lane, lane);
      const uint32_t r4 = (ln >> 3) * 4, c16 = (ln & 7) * 16, l25 = min(ln, 24u);
      const uint32_t pick = ln < 25 ? 0xeca8 : 0x9999;
      uint32_t dst[4];
#pragma unroll
      for (int i = 0; i < 4; i++) dst[i] = ring + (r4 + i) * 128 + (c16 ^ (((r4 + i) & 7) << 4));
      uint64_t pol;
      asm("createpolicy.fractional.L2::evict_first.b64 %0, 1.0;" : "=l"(pol));
      uint32_t sa = ring, phase = 1;
      const uint32_t wrap = (uint32_t)(max(B - NSTATIC * bstep, 0) + bstep - 1);
      auto next_slot = [&]() {
        const bool wrapped = sa == ring + (NSLOT - 1) * SLOT_BYTES;
        const int step = wrapped ? -(NSLOT - 1) * SLOT_BYTES : SLOT_BYTES;
        sa += step;
        phase ^= wrapped;
#pragma unroll
        for (int i = 0; i < 4; i++) dst[i] += step;
      };
      uint32_t claimer = ln;
      uint32_t drawn;
      auto draw = [&]() {
        drawn = B;
        asm volatile("{\n.reg .pred p;\nsetp.eq.u32 p, %3, 0;\n@p atom.global.inc.u32 %0, [%1], %2;\n}\n"
                     : "+r"(drawn) : "l"(counter), "r"(wrap), "r"(claimer) : "memory");
      };
      if (b >= B) draw();
      int n = kL, mean16 = 8 * kL;
      while (b < B) {
        const uint32_t e0 = nonzero_as_one(mw.x), e1 = nonzero_as_one(mw.y);
        const uint32_t e2 = nonzero_as_one(mw.z), e3 = nonzero_as_one(mw.w);
        const uint32_t nonbin = (e0 ^ mw.x) | (e1 ^ mw.y) | (e2 ^ mw.z) | (e3 ^ mw.w);
        const uint32_t sA = prmt(e0, e1, pick), sB = prmt(e2, e3, pick);
        const uint32_t pA = (sA & 0x01010101u) * 0x01010101u;
        const uint32_t pB = ((sB & 0x01010101u) + (pA >> 24)) * 0x01010101u;
        uint32_t pos = 0;
        n = 0;
#pragma unroll
        for (int k = 0; k < 4; k++) {
          const uint32_t bal = ballot_bit(pB, 0x01000000u << k);
          pos += __popc(bal & lt) << k;
          n += __popc(bal) << k;
        }
        const uint32_t general = __any_sync(0xffffffffu, nonbin != 0);
        const uint32_t aA = (pA + pos * 0x01010101u) | ~sA, aB = (pB + pos * 0x01010101u) | ~sB;
#pragma unroll
        for (int i = 0; i < 8; i++) sts8(list - 1 + prmt(i < 4 ? aA : aB, 0, 0x4440 + (i & 3)), 8 * ln + i);
        __syncwarp();

        const uint64_t src = reinterpret_cast<uint64_t>(hist) + (uint64_t)b * (kL * kD * 2);
        const bool no_carry = (uint32_t)src <= 0xffffffffu - kL * kD * 2;
        auto begin_fill = [&](uint32_t h, uint32_t part, int nc, int bt, auto extra) {
          mbar_wait(sa + S_EMPTY, phase);
          if (bt >= B) h |= part ? H_FINAL : H_FINAL | H_SELF;
          extra();
          {
            const bool wrapped = sa == ring + (NSLOT - 1) * SLOT_BYTES;
            sts32(sa + S_HDR, (h | (wrapped ? ring + 0x40000000u : sa + SLOT_BYTES)) ^ ((phase - 1) & 0xc0000000u));
          }
          sts32(sa + S_ROW + phase * 4, b | part);
          asm volatile("{\n.reg .pred p;\nsetp.eq.u32 p, %1, 0;\n@p mbarrier.arrive.shared::cta.b64 _, [%0];\n}\n"
                       :: "r"(sa + S_FULL), "r"(ln) : "memory");
          mean16 += nc - (mean16 >> 4);
          asm volatile("{\n.reg .u32 f, c;\n.reg .s32 d;\n.reg .pred p;\n"
                       "mov.u32 c, %%globaltimer_lo;\n"
                       "red.shared.max.u32 [%0], c;\n"
                       "atom.shared.add.u32 f, [%0], %1;\n"
                       "shfl.sync.idx.b32 f, f, 0, 31, 0xffffffff;\n"
                       "SPIN:\n"
                       "mov.u32 c, %%globaltimer_lo;\n"
                       "sub.s32 d, c, f;\n"
                       "setp.gt.u32 p, d, %2;\n"
                       "@p bra.uni SPIN;\n}\n" :: "r"(sb + R_PACE + ln * 4), "r"((bn >= slow_from ? mean16 * slow_pace : nc * pace16) >> 8), "r"(~(pace16 * (CHUNK / 64))) : "memory");
          if (!(part & ROW_REST)) {
            mw = load_mask(mask, min(bn, B - 1), l25);
            draw();
          }
          asm volatile("cp.async.ca.shared.global [%0], [%1], 4;"
                       :: "r"(sa + S_TGT + ln * 4), "l"(reinterpret_cast<const uint32_t*>(target) + ((uint32_t)min(bt, B - 1) * 32u + ln)) : "memory");
        };
        auto end_fill = [&](int nc) {
          cp_async_arrive_noinc(sa + S_FULL);
          next_slot();
        };
        auto usual = [&]() {
          uint32_t idx[7];
#pragma unroll
          for (int t = 0; t < 7; t++) idx[t] = lds32(list + r4 + t * 16);
          begin_fill(size_flag(n), 0, n, bn, [](){});
          const int left = n - r4;
          const uint32_t base = (uint32_t)src + c16;
          uint64_t a = (uint64_t)((uint32_t)(src >> 32) + (ln >> 5)) << 32;
          cp_group<0, false>(dst, a, idx[0], base, left, pol);
          cp_group<1, false>(dst, a, idx[1], base, left, pol);
          cp_group<2, false>(dst, a, idx[2], base, left, pol);
          cp_group<3, false>(dst, a, idx[3], base, left, pol);
          cp_group<4, true>(dst, a, idx[4], base, left, pol);
          cp_group<5, true>(dst, a, idx[5], base, left, pol);
          if (n > 96) {
            cp_group<6, true>(dst, a, idx[6], base, left, pol);
            if (n > 112) cp_group<7, true>(dst, a, lds32(list + r4 + 112), base, left, pol);
          }
          end_fill(n);
        };
        auto other = [&]() {
          int r0 = 0, nc = n <= CHUNK ? n : n <= 160 ? 64 : 96;
#pragma unroll 1
          do {
            const bool more = r0 + nc < n;
            begin_fill(general ? H_GENERAL : size_flag(max(nc, 64)), (more ? ROW_MORE : 0u) | (r0 ? ROW_REST : 0u), nc, more ? b : bn, [&]() {
#pragma unroll 1
              for (int z = ln; general && z < CHUNK; z += 32) {
                uint32_t v = 0;
                if (z < nc) {
                  uint32_t row;
                  asm volatile("ld.shared.u8 %0, [%1];" : "=r"(row) : "r"(list + r0 + z) : "memory");
                  v = __bfloat16_as_ushort(mask[(size_t)b * kL + row]);
                }
                sts16(sa + S_MASK + z * 2, v);
              }
              __syncwarp();
            });
            uint32_t rows4 = lds32(list + r0 + r4);
#pragma unroll 1
            for (int z = 0; z < CHUNK; z += 16) {
              const uint32_t now = rows4;
              rows4 = lds32(list + r0 + r4 + z + 16);
#pragma unroll
              for (int i = 0; i < 4; i++)
                asm volatile("{\n.reg .pred p;\nsetp.ge.s32 p, %2, %3;\ncp.async.cg.shared.global [%0], [%1], 16, p;\n}\n"
                             :: "r"(dst[i] + z * 128), "l"(src + c16 + prmt(now, 0, 0x4440 + i) * 128), "r"(z + r4 + i), "r"(nc) : "memory");
            }
            end_fill(nc);
            r0 += nc;
            nc = n - nc;
          } while (r0 < n);
        };
        if (n < 64 || n > CHUNK || !no_carry || general) other(); else usual();
        if (bn >= B) break;
        b = bn;
        bn = __shfl_sync(0xffffffffu, drawn, 0) + NSTATIC * bstep;
        if (bn >= B) claimer = 1;
      }
      if (b < B) mbar_wait(ring + R_START, 0);
      sts32(sa + S_HDR, b | (phase ^ 1) << 31);
      if (n <= CHUNK) {
#pragma unroll 1
        for (int i = 1; i < 2 * NSLOT; i++) next_slot();
      }
      sts32(ring + R_STOP, sa + (phase ^ 1));
      asm volatile("cp.async.wait_all;" ::: "memory");
    } else {
      uint32_t due = clock();
      int s0 = NSTATIC * bstep + (PF_EARLY * grid + blockIdx.x) * PF_ROWS;
      auto prefetch = [&]() {
        const int cnt = min(PF_ROWS, B - s0);
        if (lane == 0) {
          prefetch_l2(mask + (size_t)s0 * kL, cnt * kL * 2);
          prefetch_l2(target + (size_t)s0 * kD, cnt * kD * 2);
        }
        s0 += grid * PF_ROWS;
      };
#pragma unroll 1
      for (int j = PF_EARLY; j < PF_FAST && s0 < B; j++) {
        while ((int)(due - (uint32_t)clock()) > 0) {}
        prefetch();
        due += PF_CYCLES;
      }
      due += (PF_FAST - 1) * PF_SLOW - (PF_FAST - PF_EARLY) * PF_CYCLES + (blockIdx.x & 255) * (PF_SLOW / 256);
      asm volatile("bar.sync 6, 160;" ::: "memory");
      constexpr uint32_t WHERE = 0x3ffff;
      const uint32_t mine = __shfl_sync(0xffffffffu, sb + min(lane, NCW - 1) * RING_BYTES, lane);
      uint32_t at = mine | ~WHERE;
      const uint32_t ln = __shfl_sync(0xffffffffu, lane, lane);
      const uint32_t rd = __shfl_sync(0xffffffffu, sums_at(2 * (lane & 7)) + (lane >> 3) * 512, lane);
      uint4 bf = lds128(sb + SCALES + lane * 16);
      bf.x += grid >> 20;
      bf.z += grid >> 20;
      uint32_t* const dst = reinterpret_cast<uint32_t*>(out) + ((lane & 1) * 16 + (lane & 2) * 4 + (lane >> 2));
      uint32_t idle = 0;
#pragma unroll 1
      while (true) {
        const uint32_t go = __reduce_max_sync(0xffffffffu, mbar_test((at & (WHERE - 1)) + S_EMPTY, at & 1) ? at : 0u);
        if (go) {
          const uint32_t sa = go & (WHERE - 1);
          const uint32_t row = lds32(sa + S_ROW + 4 - (go & 1) * 4);
          uint32_t u[8][4];
#pragma unroll
          for (int i = 0; i < 8; i++) ldsm_x4(((sa + rd) ^ (i & 1) * 16) + (i & 2) * 128 + (i >> 2) * 2048, u[i][0], u[i][1], u[i][2], u[i][3]);
          cut_here(idle, sa == 0);
          float c[4][4];
#pragma unroll
          for (int j = 0; j < 4; j++) hmma<true>(c[j], u[j], bf.x, bf.y);
#pragma unroll
          for (int j = 0; j < 4; j++) hmma<false>(c[j], u[4 + j], bf.z, bf.w);
          float e0 = c[0][0] + c[0][3], e1 = c[1][0] + c[1][3];
          if (ln & 2) { e0 = c[2][0] + c[2][3]; e1 = c[3][0] + c[3][3]; }
          __syncwarp();
          if (ln == 0) mbar_arrive(sa + S_FULL);
          if (at == go) at = (sa == mine + (NSLOT - 1) * SLOT_BYTES ? (at - (NSLOT - 1) * SLOT_BYTES) ^ 1 : at + SLOT_BYTES) - (WHERE + 1);
          if (__builtin_expect(row >= ROW_REST, 0)) {
            const uint32_t carry = __reduce_max_sync(0xffffffffu, mine <= sa ? mine : 0u) + R_CARRY + ln * 8;
            if (row & ROW_REST) { e0 += __uint_as_float(lds32(carry)); e1 += __uint_as_float(lds32(carry + 4)); }
            sts32(carry, __float_as_uint(e0));
            sts32(carry + 4, __float_as_uint(e1));
          }
          if (row < ROW_MORE) dst[(row & (ROW_REST - 1)) * 32] = pack_bf16(e0, e1);
        } else {
          if (__all_sync(0xffffffffu, lds32(mine + R_STOP) == (at & WHERE))) break;
          if (++idle > 0x4000000) __trap();
          if (s0 < B && (int)(due - (uint32_t)clock()) <= 0) { prefetch(); due += PF_SLOW; }
          if (RED_SLEEP) __nanosleep(RED_SLEEP);
        }
      }
    }
  }
}

}

extern "C" void kernel_launch(void* const* d_in, const int* in_sizes, int n_in, void* d_out, int out_size) {
  const __nv_bfloat16* target = (const __nv_bfloat16*)d_in[0];
  const __nv_bfloat16* hist = (const __nv_bfloat16*)d_in[1];
  const __nv_bfloat16* mask = (const __nv_bfloat16*)d_in[2];
  const __nv_bfloat16* w1 = (const __nv_bfloat16*)d_in[3];
  const __nv_bfloat16* b1 = (const __nv_bfloat16*)d_in[4];
  const __nv_bfloat16* w2 = (const __nv_bfloat16*)d_in[5];
  const __nv_bfloat16* b2 = (const __nv_bfloat16*)d_in[6];
  const int B = in_sizes[0] / din::kD;
  if (B <= 0) return;
  static int sms = 0, pace = 0;
  static unsigned int* counter = nullptr;
  if (sms == 0) {
    int dev = 0, khz = 0, bits = 0;
    cudaGetDevice(&dev);
    cudaDeviceGetAttribute(&sms, cudaDevAttrMultiProcessorCount, dev);
    cudaDeviceGetAttribute(&khz, cudaDevAttrMemoryClockRate, dev);
    cudaDeviceGetAttribute(&bits, cudaDevAttrGlobalMemoryBusWidth, dev);
    if (khz > 0 && bits > 0) pace = (int)(16.0 * 128.0 * sms / (khz * 1e-6 * 2.0 * bits / 8.0));
    if (pace > 256) pace = 0;
    cudaGetSymbolAddress((void**)&counter, din::g_next);
    cudaFuncSetAttribute(din::din_kernel, cudaFuncAttributeMaxDynamicSharedMemorySize, din::SMEM_BYTES);
  }
  const long long early = (long long)(din::NSTATIC * NCW + PF_EARLY * PF_ROWS) * sms, line = 128LL * sms;
  long long pf_mask = (early * din::kL * 2 + line - 1) / line, pf_tgt = early * din::kD * 2 / line;
  if (pf_mask > (long long)B * din::kL * 2 / line) pf_mask = (long long)B * din::kL * 2 / line;
  if (pf_tgt > (long long)B * din::kD * 2 / line) pf_tgt = (long long)B * din::kD * 2 / line;
  din::din_kernel<<<sms, din::NTHREADS, din::SMEM_BYTES>>>(mask, target, B, sms, (uint32_t)pf_mask * 128, (uint32_t)pf_tgt * 128,
                                                          w1, hist, b1, w2, b2, (__nv_bfloat16*)d_out, counter, pace * 16,
                                                          pace + pace * SLOW_BY / 80, B - SLOW_ROUNDS * NCW * sms);
}
```

```cpp
#include <cuda_runtime.h>
#include <cuda_bf16.h>
#include <stdint.h>

namespace din {

constexpr int kL = 200, kD = 64;
#define NCW 3
#define NSLOT 3
constexpr int CHUNK = 128;
constexpr int NTHREADS = NCW * 128 + 128;
#define PREGS 56
#define CREGS 152
constexpr int PROD_REGS = PREGS, CONS_REGS = CREGS;
#define PF_ROWS 8
#define PF_FAST 10
#define PF_SLOW 2000
#define PF_CYCLES 280
#define RED_SLEEP 100
#define K_SEL 1
#define K_LO2 2
#define K_HI1 2
#define K_HI2 2
#define K_NX 2
#define K_BAR 1
#define K_TOP 1
#define NA 4
#define KL 2
#define S0 1
#define D0 5
#define KC 4
#define PF_EARLY 3
#define SLOW_ROUNDS 5
#define SLOW_BY 13
constexpr int NSTATIC = 2;
constexpr int S_TGT = CHUNK * 128;
constexpr int S_HDR = S_TGT + 128;
constexpr int S_FULL = S_HDR + 8;
constexpr int S_EMPTY = S_HDR + 16;
constexpr int S_ROW = S_HDR + 24;
constexpr int S_MASK = S_TGT + 256;
constexpr int S_OUT = S_TGT + 1024;
constexpr int SLOT_BYTES = S_OUT + 4096;
constexpr int RING_BYTES_ = NSLOT * SLOT_BYTES;
constexpr int R_PACE = 2 * RING_BYTES_ + S_TGT + 768;
constexpr int R_START = S_HDR + 32;
constexpr int R_STOP = S_HDR + 44;
constexpr int R_LIST = S_TGT + 512;
constexpr int R_VEC = S_TGT + 768;
constexpr int R_SEL = S_TGT + 896;
constexpr int R_CARRY = SLOT_BYTES + S_TGT + 512;
constexpr int R_TGT0 = (NSLOT - 1) * SLOT_BYTES + S_OUT;
constexpr int RING_BYTES = NSLOT * SLOT_BYTES;
constexpr int SCALES = NCW * RING_BYTES + 32768;
constexpr int SMEM_BYTES = SCALES + 512 + 1024;
__device__ constexpr int w1_at(int i) { return NCW * RING_BYTES + i * 8192; }
static_assert(SMEM_BYTES <= 232448, "shared memory");
constexpr uint32_t H_12 = 0x1f, H_13 = 0x20, H_14 = 0x40, H_15 = 0x80, H_16 = 0x100;
constexpr uint32_t H_GENERAL = 1u << 18, H_FINAL = 1u << 19, H_SELF = 1u << 20, H_NEXT = 0x3fc3fc00;
__device__ __forceinline__ uint32_t size_flag(int rows) { return 1u << ((rows - 57) >> 3); }
constexpr uint32_t ROW_REST = 1u << 30, ROW_MORE = 1u << 31;

__device__ unsigned int g_next;

#define STR2(x) #x
#define STR(x) STR2(x)
template<int V> struct Int { static constexpr int value = V; };
template<int G> __device__ __forceinline__ void g1_bias(float* d, const uint32_t (&bq)[4], uint32_t loSel);
template<int G> __device__ __forceinline__ void g1_step(float* d, const uint32_t* a, uint32_t loH, uint32_t hiH);
template<> __device__ __forceinline__ void g1_bias<4>(float* d, const uint32_t (&bq)[4], uint32_t loSel) {
  asm volatile("{\n.reg .b64 db;\n.reg .b32 zr;\n"
    "mov.b32 zr, 0;\nmov.b64 db, {%20, zr};\n"
    "wgmma.mma_async.sync.aligned.m64n32k16.f32.bf16.bf16 {%0, %1, %2, %3, %4, %5, %6, %7, %8, %9, %10, %11, %12, %13, %14, %15}, {%16, %17, %18, %19}, db, 0, 1, 1, 0;\n}\n"
    : "=f"(d[0]), "=f"(d[1]), "=f"(d[2]), "=f"(d[3]), "=f"(d[4]), "=f"(d[5]), "=f"(d[6]), "=f"(d[7]), "=f"(d[8]), "=f"(d[9]), "=f"(d[10]), "=f"(d[11]), "=f"(d[12]), "=f"(d[13]), "=f"(d[14]), "=f"(d[15])
    : "r"(bq[0]), "r"(bq[1]), "r"(bq[2]), "r"(bq[3]), "r"(loSel)
    : "memory");
}
template<> __device__ __forceinline__ void g1_bias<8>(float* d, const uint32_t (&bq)[4], uint32_t loSel) {
  asm volatile("{\n.reg .b64 db;\n.reg .b32 zr;\n"
    "mov.b32 zr, 0;\nmov.b64 db, {%36, zr};\n"
    "wgmma.mma_async.sync.aligned.m64n64k16.f32.bf16.bf16 {%0, %1, %2, %3, %4, %5, %6, %7, %8, %9, %10, %11, %12, %13, %14, %15, %16, %17, %18, %19, %20, %21, %22, %23, %24, %25, %26, %27, %28, %29, %30, %31}, {%32, %33, %34, %35}, db, 0, 1, 1, 0;\n}\n"
    : "=f"(d[0]), "=f"(d[1]), "=f"(d[2]), "=f"(d[3]), "=f"(d[4]), "=f"(d[5]), "=f"(d[6]), "=f"(d[7]), "=f"(d[8]), "=f"(d[9]), "=f"(d[10]), "=f"(d[11]), "=f"(d[12]), "=f"(d[13]), "=f"(d[14]), "=f"(d[15]), "=f"(d[16]), "=f"(d[17]), "=f"(d[18]), "=f"(d[19]), "=f"(d[20]), "=f"(d[21]), "=f"(d[22]), "=f"(d[23]), "=f"(d[24]), "=f"(d[25]), "=f"(d[26]), "=f"(d[27]), "=f"(d[28]), "=f"(d[29]), "=f"(d[30]), "=f"(d[31])
    : "r"(bq[0]), "r"(bq[1]), "r"(bq[2]), "r"(bq[3]), "r"(loSel)
    : "memory");
}
template<> __device__ __forceinline__ void g1_bias<9>(float* d, const uint32_t (&bq)[4], uint32_t loSel) {
  asm volatile("{\n.reg .b64 db;\n.reg .b32 zr;\n"
    "mov.b32 zr, 0;\nmov.b64 db, {%40, zr};\n"
    "wgmma.mma_async.sync.aligned.m64n72k16.f32.bf16.bf16 {%0, %1, %2, %3, %4, %5, %6, %7, %8, %9, %10, %11, %12, %13, %14, %15, %16, %17, %18, %19, %20, %21, %22, %23, %24, %25, %26, %27, %28, %29, %30, %31, %32, %33, %34, %35}, {%36, %37, %38, %39}, db, 0, 1, 1, 0;\n}\n"
    : "=f"(d[0]), "=f"(d[1]), "=f"(d[2]), "=f"(d[3]), "=f"(d[4]), "=f"(d[5]), "=f"(d[6]), "=f"(d[7]), "=f"(d[8]), "=f"(d[9]), "=f"(d[10]), "=f"(d[11]), "=f"(d[12]), "=f"(d[13]), "=f"(d[14]), "=f"(d[15]), "=f"(d[16]), "=f"(d[17]), "=f"(d[18]), "=f"(d[19]), "=f"(d[20]), "=f"(d[21]), "=f"(d[22]), "=f"(d[23]), "=f"(d[24]), "=f"(d[25]), "=f"(d[26]), "=f"(d[27]), "=f"(d[28]), "=f"(d[29]), "=f"(d[30]), "=f"(d[31]), "=f"(d[32]), "=f"(d[33]), "=f"(d[34]), "=f"(d[35])
    : "r"(bq[0]), "r"(bq[1]), "r"(bq[2]), "r"(bq[3]), "r"(loSel)
    : "memory");
}
template<> __device__ __forceinline__ void g1_bias<10>(float* d, const uint32_t (&bq)[4], uint32_t loSel) {
  asm volatile("{\n.reg .b64 db;\n.reg .b32 zr;\n"
    "mov.b32 zr, 0;\nmov.b64 db, {%44, zr};\n"
    "wgmma.mma_async.sync.aligned.m64n80k16.f32.bf16.bf16 {%0, %1, %2, %3, %4, %5, %6, %7, %8, %9, %10, %11, %12, %13, %14, %15, %16, %17, %18, %19, %20, %21, %22, %23, %24, %25, %26, %27, %28, %29, %30, %31, %32, %33, %34, %35, %36, %37, %38, %39}, {%40, %41, %42, %43}, db, 0, 1, 1, 0;\n}\n"
    : "=f"(d[0]), "=f"(d[1]), "=f"(d[2]), "=f"(d[3]), "=f"(d[4]), "=f"(d[5]), "=f"(d[6]), "=f"(d[7]), "=f"(d[8]), "=f"(d[9]), "=f"(d[10]), "=f"(d[11]), "=f"(d[12]), "=f"(d[13]), "=f"(d[14]), "=f"(d[15]), "=f"(d[16]), "=f"(d[17]), "=f"(d[18]), "=f"(d[19]), "=f"(d[20]), "=f"(d[21]), "=f"(d[22]), "=f"(d[23]), "=f"(d[24]), "=f"(d[25]), "=f"(d[26]), "=f"(d[27]), "=f"(d[28]), "=f"(d[29]), "=f"(d[30]), "=f"(d[31]), "=f"(d[32]), "=f"(d[33]), "=f"(d[34]), "=f"(d[35]), "=f"(d[36]), "=f"(d[37]), "=f"(d[38]), "=f"(d[39])
    : "r"(bq[0]), "r"(bq[1]), "r"(bq[2]), "r"(bq[3]), "r"(loSel)
    : "memory");
}
template<> __device__ __forceinline__ void g1_bias<11>(float* d, const uint32_t (&bq)[4], uint32_t loSel) {
  asm volatile("{\n.reg .b64 db;\n.reg .b32 zr;\n"
    "mov.b32 zr, 0;\nmov.b64 db, {%48, zr};\n"
    "wgmma.mma_async.sync.aligned.m64n88k16.f32.bf16.bf16 {%0, %1, %2, %3, %4, %5, %6, %7, %8, %9, %10, %11, %12, %13, %14, %15, %16, %17, %18, %19, %20, %21, %22, %23, %24, %25, %26, %27, %28, %29, %30, %31, %32, %33, %34, %35, %36, %37, %38, %39, %40, %41, %42, %43}, {%44, %45, %46, %47}, db, 0, 1, 1, 0;\n}\n"
    : "=f"(d[0]), "=f"(d[1]), "=f"(d[2]), "=f"(d[3]), "=f"(d[4]), "=f"(d[5]), "=f"(d[6]), "=f"(d[7]), "=f"(d[8]), "=f"(d[9]), "=f"(d[10]), "=f"(d[11]), "=f"(d[12]), "=f"(d[13]), "=f"(d[14]), "=f"(d[15]), "=f"(d[16]), "=f"(d[17]), "=f"(d[18]), "=f"(d[19]), "=f"(d[20]), "=f"(d[21]), "=f"(d[22]), "=f"(d[23]), "=f"(d[24]), "=f"(d[25]), "=f"(d[26]), "=f"(d[27]), "=f"(d[28]), "=f"(d[29]), "=f"(d[30]), "=f"(d[31]), "=f"(d[32]), "=f"(d[33]), "=f"(d[34]), "=f"(d[35]), "=f"(d[36]), "=f"(d[37]), "=f"(d[38]), "=f"(d[39]), "=f"(d[40]), "=f"(d[41]), "=f"(d[42]), "=f"(d[43])
    : "r"(bq[0]), "r"(bq[1]), "r"(bq[2]), "r"(bq[3]), "r"(loSel)
    : "memory");
}
template<> __device__ __forceinline__ void g1_bias<12>(float* d, const uint32_t (&bq)[4], uint32_t loSel) {
  asm volatile("{\n.reg .b64 db;\n.reg .b32 zr;\n"
    "mov.b32 zr, 0;\nmov.b64 db, {%52, zr};\n"
    "wgmma.mma_async.sync.aligned.m64n96k16.f32.bf16.bf16 {%0, %1, %2, %3, %4, %5, %6, %7, %8, %9, %10, %11, %12, %13, %14, %15, %16, %17, %18, %19, %20, %21, %22, %23, %24, %25, %26, %27, %28, %29, %30, %31, %32, %33, %34, %35, %36, %37, %38, %39, %40, %41, %42, %43, %44, %45, %46, %47}, {%48, %49, %50, %51}, db, 0, 1, 1, 0;\n}\n"
    : "=f"(d[0]), "=f"(d[1]), "=f"(d[2]), "=f"(d[3]), "=f"(d[4]), "=f"(d[5]), "=f"(d[6]), "=f"(d[7]), "=f"(d[8]), "=f"(d[9]), "=f"(d[10]), "=f"(d[11]), "=f"(d[12]), "=f"(d[13]), "=f"(d[14]), "=f"(d[15]), "=f"(d[16]), "=f"(d[17]), "=f"(d[18]), "=f"(d[19]), "=f"(d[20]), "=f"(d[21]), "=f"(d[22]), "=f"(d[23]), "=f"(d[24]), "=f"(d[25]), "=f"(d[26]), "=f"(d[27]), "=f"(d[28]), "=f"(d[29]), "=f"(d[30]), "=f"(d[31]), "=f"(d[32]), "=f"(d[33]), "=f"(d[34]), "=f"(d[35]), "=f"(d[36]), "=f"(d[37]), "=f"(d[38]), "=f"(d[39]), "=f"(d[40]), "=f"(d[41]), "=f"(d[42]), "=f"(d[43]), "=f"(d[44]), "=f"(d[45]), "=f"(d[46]), "=f"(d[47])
    : "r"(bq[0]), "r"(bq[1]), "r"(bq[2]), "r"(bq[3]), "r"(loSel)
    : "memory");
}
template<> __device__ __forceinline__ void g1_step<4>(float* d, const uint32_t* a, uint32_t loH, uint32_t hiH) {
  asm volatile("{\n.reg .b64 db;\nmov.b64 db, {%20, %21};\n"
    "wgmma.mma_async.sync.aligned.m64n32k16.f32.bf16.bf16 {%0, %1, %2, %3, %4, %5, %6, %7, %8, %9, %10, %11, %12, %13, %14, %15}, {%16, %17, %18, %19}, db, 1, 1, 1, 0;\n}\n"
    : "+f"(d[0]), "+f"(d[1]), "+f"(d[2]), "+f"(d[3]), "+f"(d[4]), "+f"(d[5]), "+f"(d[6]), "+f"(d[7]), "+f"(d[8]), "+f"(d[9]), "+f"(d[10]), "+f"(d[11]), "+f"(d[12]), "+f"(d[13]), "+f"(d[14]), "+f"(d[15])
    : "r"(a[0]), "r"(a[1]), "r"(a[2]), "r"(a[3]), "r"(loH), "r"(hiH)
    : "memory");
}
template<> __device__ __forceinline__ void g1_step<8>(float* d, const uint32_t* a, uint32_t loH, uint32_t hiH) {
  asm volatile("{\n.reg .b64 db;\nmov.b64 db, {%36, %37};\n"
    "wgmma.mma_async.sync.aligned.m64n64k16.f32.bf16.bf16 {%0, %1, %2, %3, %4, %5, %6, %7, %8, %9, %10, %11, %12, %13, %14, %15, %16, %17, %18, %19, %20, %21, %22, %23, %24, %25, %26, %27, %28, %29, %30, %31}, {%32, %33, %34, %35}, db, 1, 1, 1, 0;\n}\n"
    : "+f"(d[0]), "+f"(d[1]), "+f"(d[2]), "+f"(d[3]), "+f"(d[4]), "+f"(d[5]), "+f"(d[6]), "+f"(d[7]), "+f"(d[8]), "+f"(d[9]), "+f"(d[10]), "+f"(d[11]), "+f"(d[12]), "+f"(d[13]), "+f"(d[14]), "+f"(d[15]), "+f"(d[16]), "+f"(d[17]), "+f"(d[18]), "+f"(d[19]), "+f"(d[20]), "+f"(d[21]), "+f"(d[22]), "+f"(d[23]), "+f"(d[24]), "+f"(d[25]), "+f"(d[26]), "+f"(d[27]), "+f"(d[28]), "+f"(d[29]), "+f"(d[30]), "+f"(d[31])
    : "r"(a[0]), "r"(a[1]), "r"(a[2]), "r"(a[3]), "r"(loH), "r"(hiH)
    : "memory");
}
template<> __device__ __forceinline__ void g1_step<9>(float* d, const uint32_t* a, uint32_t loH, uint32_t hiH) {
  asm volatile("{\n.reg .b64 db;\nmov.b64 db, {%40, %41};\n"
    "wgmma.mma_async.sync.aligned.m64n72k16.f32.bf16.bf16 {%0, %1, %2, %3, %4, %5, %6, %7, %8, %9, %10, %11, %12, %13, %14, %15, %16, %17, %18, %19, %20, %21, %22, %23, %24, %25, %26, %27, %28, %29, %30, %31, %32, %33, %34, %35}, {%36, %37, %38, %39}, db, 1, 1, 1, 0;\n}\n"
    : "+f"(d[0]), "+f"(d[1]), "+f"(d[2]), "+f"(d[3]), "+f"(d[4]), "+f"(d[5]), "+f"(d[6]), "+f"(d[7]), "+f"(d[8]), "+f"(d[9]), "+f"(d[10]), "+f"(d[11]), "+f"(d[12]), "+f"(d[13]), "+f"(d[14]), "+f"(d[15]), "+f"(d[16]), "+f"(d[17]), "+f"(d[18]), "+f"(d[19]), "+f"(d[20]), "+f"(d[21]), "+f"(d[22]), "+f"(d[23]), "+f"(d[24]), "+f"(d[25]), "+f"(d[26]), "+f"(d[27]), "+f"(d[28]), "+f"(d[29]), "+f"(d[30]), "+f"(d[31]), "+f"(d[32]), "+f"(d[33]), "+f"(d[34]), "+f"(d[35])
    : "r"(a[0]), "r"(a[1]), "r"(a[2]), "r"(a[3]), "r"(loH), "r"(hiH)
    : "memory");
}
template<> __device__ __forceinline__ void g1_step<10>(float* d, const uint32_t* a, uint32_t loH, uint32_t hiH) {
  asm volatile("{\n.reg .b64 db;\nmov.b64 db, {%44, %45};\n"
    "wgmma.mma_async.sync.aligned.m64n80k16.f32.bf16.bf16 {%0, %1, %2, %3, %4, %5, %6, %7, %8, %9, %10, %11, %12, %13, %14, %15, %16, %17, %18, %19, %20, %21, %22, %23, %24, %25, %26, %27, %28, %29, %30, %31, %32, %33, %34, %35, %36, %37, %38, %39}, {%40, %41, %42, %43}, db, 1, 1, 1, 0;\n}\n"
    : "+f"(d[0]), "+f"(d[1]), "+f"(d[2]), "+f"(d[3]), "+f"(d[4]), "+f"(d[5]), "+f"(d[6]), "+f"(d[7]), "+f"(d[8]), "+f"(d[9]), "+f"(d[10]), "+f"(d[11]), "+f"(d[12]), "+f"(d[13]), "+f"(d[14]), "+f"(d[15]), "+f"(d[16]), "+f"(d[17]), "+f"(d[18]), "+f"(d[19]), "+f"(d[20]), "+f"(d[21]), "+f"(d[22]), "+f"(d[23]), "+f"(d[24]), "+f"(d[25]), "+f"(d[26]), "+f"(d[27]), "+f"(d[28]), "+f"(d[29]), "+f"(d[30]), "+f"(d[31]), "+f"(d[32]), "+f"(d[33]), "+f"(d[34]), "+f"(d[35]), "+f"(d[36]), "+f"(d[37]), "+f"(d[38]), "+f"(d[39])
    : "r"(a[0]), "r"(a[1]), "r"(a[2]), "r"(a[3]), "r"(loH), "r"(hiH)
    : "memory");
}
template<> __device__ __forceinline__ void g1_step<11>(float* d, const uint32_t* a, uint32_t loH, uint32_t hiH) {
  asm volatile("{\n.reg .b64 db;\nmov.b64 db, {%48, %49};\n"
    "wgmma.mma_async.sync.aligned.m64n88k16.f32.bf16.bf16 {%0, %1, %2, %3, %4, %5, %6, %7, %8, %9, %10, %11, %12, %13, %14, %15, %16, %17, %18, %19, %20, %21, %22, %23, %24, %25, %26, %27, %28, %29, %30, %31, %32, %33, %34, %35, %36, %37, %38, %39, %40, %41, %42, %43}, {%44, %45, %46, %47}, db, 1, 1, 1, 0;\n}\n"
    : "+f"(d[0]), "+f"(d[1]), "+f"(d[2]), "+f"(d[3]), "+f"(d[4]), "+f"(d[5]), "+f"(d[6]), "+f"(d[7]), "+f"(d[8]), "+f"(d[9]), "+f"(d[10]), "+f"(d[11]), "+f"(d[12]), "+f"(d[13]), "+f"(d[14]), "+f"(d[15]), "+f"(d[16]), "+f"(d[17]), "+f"(d[18]), "+f"(d[19]), "+f"(d[20]), "+f"(d[21]), "+f"(d[22]), "+f"(d[23]), "+f"(d[24]), "+f"(d[25]), "+f"(d[26]), "+f"(d[27]), "+f"(d[28]), "+f"(d[29]), "+f"(d[30]), "+f"(d[31]), "+f"(d[32]), "+f"(d[33]), "+f"(d[34]), "+f"(d[35]), "+f"(d[36]), "+f"(d[37]), "+f"(d[38]), "+f"(d[39]), "+f"(d[40]), "+f"(d[41]), "+f"(d[42]), "+f"(d[43])
    : "r"(a[0]), "r"(a[1]), "r"(a[2]), "r"(a[3]), "r"(loH), "r"(hiH)
    : "memory");
}
template<> __device__ __forceinline__ void g1_step<12>(float* d, const uint32_t* a, uint32_t loH, uint32_t hiH) {
  asm volatile("{\n.reg .b64 db;\nmov.b64 db, {%52, %53};\n"
    "wgmma.mma_async.sync.aligned.m64n96k16.f32.bf16.bf16 {%0, %1, %2, %3, %4, %5, %6, %7, %8, %9, %10, %11, %12, %13, %14, %15, %16, %17, %18, %19, %20, %21, %22, %23, %24, %25, %26, %27, %28, %29, %30, %31, %32, %33, %34, %35, %36, %37, %38, %39, %40, %41, %42, %43, %44, %45, %46, %47}, {%48, %49, %50, %51}, db, 1, 1, 1, 0;\n}\n"
    : "+f"(d[0]), "+f"(d[1]), "+f"(d[2]), "+f"(d[3]), "+f"(d[4]), "+f"(d[5]), "+f"(d[6]), "+f"(d[7]), "+f"(d[8]), "+f"(d[9]), "+f"(d[10]), "+f"(d[11]), "+f"(d[12]), "+f"(d[13]), "+f"(d[14]), "+f"(d[15]), "+f"(d[16]), "+f"(d[17]), "+f"(d[18]), "+f"(d[19]), "+f"(d[20]), "+f"(d[21]), "+f"(d[22]), "+f"(d[23]), "+f"(d[24]), "+f"(d[25]), "+f"(d[26]), "+f"(d[27]), "+f"(d[28]), "+f"(d[29]), "+f"(d[30]), "+f"(d[31]), "+f"(d[32]), "+f"(d[33]), "+f"(d[34]), "+f"(d[35]), "+f"(d[36]), "+f"(d[37]), "+f"(d[38]), "+f"(d[39]), "+f"(d[40]), "+f"(d[41]), "+f"(d[42]), "+f"(d[43]), "+f"(d[44]), "+f"(d[45]), "+f"(d[46]), "+f"(d[47])
    : "r"(a[0]), "r"(a[1]), "r"(a[2]), "r"(a[3]), "r"(loH), "r"(hiH)
    : "memory");
}
__device__ __forceinline__ void g2_first(float (&o)[16], const uint32_t* a, uint32_t loH, uint32_t meta, uint32_t hiH) {
  asm volatile("{\n.reg .b64 db;\nmov.b64 db, {%20, %22};\n"
    "wgmma.mma_async.sp.sync.aligned.m64n32k32.f32.bf16.bf16 {%0, %1, %2, %3, %4, %5, %6, %7, %8, %9, %10, %11, %12, %13, %14, %15}, {%16, %17, %18, %19}, db, %21, 0, 0, 1, 1, 1;\n}\n"
    : "=f"(o[0]), "=f"(o[1]), "=f"(o[2]), "=f"(o[3]), "=f"(o[4]), "=f"(o[5]), "=f"(o[6]), "=f"(o[7]), "=f"(o[8]), "=f"(o[9]), "=f"(o[10]), "=f"(o[11]), "=f"(o[12]), "=f"(o[13]), "=f"(o[14]), "=f"(o[15])
    : "r"(a[0]), "r"(a[1]), "r"(a[2]), "r"(a[3]), "r"(loH), "r"(meta), "r"(hiH)
    : "memory");
}
__device__ __forceinline__ void g2_more(float (&o)[16], const uint32_t* a, uint32_t loH, uint32_t meta, uint32_t hiH) {
  asm volatile("{\n.reg .b64 db;\nmov.b64 db, {%20, %22};\n"
    "wgmma.mma_async.sp.sync.aligned.m64n32k32.f32.bf16.bf16 {%0, %1, %2, %3, %4, %5, %6, %7, %8, %9, %10, %11, %12, %13, %14, %15}, {%16, %17, %18, %19}, db, %21, 0, 1, 1, 1, 1;\n}\n"
    : "+f"(o[0]), "+f"(o[1]), "+f"(o[2]), "+f"(o[3]), "+f"(o[4]), "+f"(o[5]), "+f"(o[6]), "+f"(o[7]), "+f"(o[8]), "+f"(o[9]), "+f"(o[10]), "+f"(o[11]), "+f"(o[12]), "+f"(o[13]), "+f"(o[14]), "+f"(o[15])
    : "r"(a[0]), "r"(a[1]), "r"(a[2]), "r"(a[3]), "r"(loH), "r"(meta), "r"(hiH)
    : "memory");
}
template<int N> __device__ __forceinline__ void mma_wait(float* d, Int<4>) {
  asm volatile("wgmma.wait_group.sync.aligned %16;"
    : "+f"(d[0]), "+f"(d[1]), "+f"(d[2]), "+f"(d[3]), "+f"(d[4]), "+f"(d[5]), "+f"(d[6]), "+f"(d[7]), "+f"(d[8]), "+f"(d[9]), "+f"(d[10]), "+f"(d[11]), "+f"(d[12]), "+f"(d[13]), "+f"(d[14]), "+f"(d[15])
    : "n"(N) : "memory");
}
template<int N> __device__ __forceinline__ void mma_wait(float* d, Int<8>) {
  asm volatile("wgmma.wait_group.sync.aligned %32;"
    : "+f"(d[0]), "+f"(d[1]), "+f"(d[2]), "+f"(d[3]), "+f"(d[4]), "+f"(d[5]), "+f"(d[6]), "+f"(d[7]), "+f"(d[8]), "+f"(d[9]), "+f"(d[10]), "+f"(d[11]), "+f"(d[12]), "+f"(d[13]), "+f"(d[14]), "+f"(d[15]), "+f"(d[16]), "+f"(d[17]), "+f"(d[18]), "+f"(d[19]), "+f"(d[20]), "+f"(d[21]), "+f"(d[22]), "+f"(d[23]), "+f"(d[24]), "+f"(d[25]), "+f"(d[26]), "+f"(d[27]), "+f"(d[28]), "+f"(d[29]), "+f"(d[30]), "+f"(d[31])
    : "n"(N) : "memory");
}
template<int N> __device__ __forceinline__ void mma_wait(float* d, Int<9>) {
  asm volatile("wgmma.wait_group.sync.aligned %36;"
    : "+f"(d[0]), "+f"(d[1]), "+f"(d[2]), "+f"(d[3]), "+f"(d[4]), "+f"(d[5]), "+f"(d[6]), "+f"(d[7]), "+f"(d[8]), "+f"(d[9]), "+f"(d[10]), "+f"(d[11]), "+f"(d[12]), "+f"(d[13]), "+f"(d[14]), "+f"(d[15]), "+f"(d[16]), "+f"(d[17]), "+f"(d[18]), "+f"(d[19]), "+f"(d[20]), "+f"(d[21]), "+f"(d[22]), "+f"(d[23]), "+f"(d[24]), "+f"(d[25]), "+f"(d[26]), "+f"(d[27]), "+f"(d[28]), "+f"(d[29]), "+f"(d[30]), "+f"(d[31]), "+f"(d[32]), "+f"(d[33]), "+f"(d[34]), "+f"(d[35])
    : "n"(N) : "memory");
}
template<int N> __device__ __forceinline__ void mma_wait(float* d, Int<10>) {
  asm volatile("wgmma.wait_group.sync.aligned %40;"
    : "+f"(d[0]), "+f"(d[1]), "+f"(d[2]), "+f"(d[3]), "+f"(d[4]), "+f"(d[5]), "+f"(d[6]), "+f"(d[7]), "+f"(d[8]), "+f"(d[9]), "+f"(d[10]), "+f"(d[11]), "+f"(d[12]), "+f"(d[13]), "+f"(d[14]), "+f"(d[15]), "+f"(d[16]), "+f"(d[17]), "+f"(d[18]), "+f"(d[19]), "+f"(d[20]), "+f"(d[21]), "+f"(d[22]), "+f"(d[23]), "+f"(d[24]), "+f"(d[25]), "+f"(d[26]), "+f"(d[27]), "+f"(d[28]), "+f"(d[29]), "+f"(d[30]), "+f"(d[31]), "+f"(d[32]), "+f"(d[33]), "+f"(d[34]), "+f"(d[35]), "+f"(d[36]), "+f"(d[37]), "+f"(d[38]), "+f"(d[39])
    : "n"(N) : "memory");
}
template<int N> __device__ __forceinline__ void mma_wait(float* d, Int<11>) {
  asm volatile("wgmma.wait_group.sync.aligned %44;"
    : "+f"(d[0]), "+f"(d[1]), "+f"(d[2]), "+f"(d[3]), "+f"(d[4]), "+f"(d[5]), "+f"(d[6]), "+f"(d[7]), "+f"(d[8]), "+f"(d[9]), "+f"(d[10]), "+f"(d[11]), "+f"(d[12]), "+f"(d[13]), "+f"(d[14]), "+f"(d[15]), "+f"(d[16]), "+f"(d[17]), "+f"(d[18]), "+f"(d[19]), "+f"(d[20]), "+f"(d[21]), "+f"(d[22]), "+f"(d[23]), "+f"(d[24]), "+f"(d[25]), "+f"(d[26]), "+f"(d[27]), "+f"(d[28]), "+f"(d[29]), "+f"(d[30]), "+f"(d[31]), "+f"(d[32]), "+f"(d[33]), "+f"(d[34]), "+f"(d[35]), "+f"(d[36]), "+f"(d[37]), "+f"(d[38]), "+f"(d[39]), "+f"(d[40]), "+f"(d[41]), "+f"(d[42]), "+f"(d[43])
    : "n"(N) : "memory");
}
template<int N> __device__ __forceinline__ void mma_wait(float* d, Int<12>) {
  asm volatile("wgmma.wait_group.sync.aligned %48;"
    : "+f"(d[0]), "+f"(d[1]), "+f"(d[2]), "+f"(d[3]), "+f"(d[4]), "+f"(d[5]), "+f"(d[6]), "+f"(d[7]), "+f"(d[8]), "+f"(d[9]), "+f"(d[10]), "+f"(d[11]), "+f"(d[12]), "+f"(d[13]), "+f"(d[14]), "+f"(d[15]), "+f"(d[16]), "+f"(d[17]), "+f"(d[18]), "+f"(d[19]), "+f"(d[20]), "+f"(d[21]), "+f"(d[22]), "+f"(d[23]), "+f"(d[24]), "+f"(d[25]), "+f"(d[26]), "+f"(d[27]), "+f"(d[28]), "+f"(d[29]), "+f"(d[30]), "+f"(d[31]), "+f"(d[32]), "+f"(d[33]), "+f"(d[34]), "+f"(d[35]), "+f"(d[36]), "+f"(d[37]), "+f"(d[38]), "+f"(d[39]), "+f"(d[40]), "+f"(d[41]), "+f"(d[42]), "+f"(d[43]), "+f"(d[44]), "+f"(d[45]), "+f"(d[46]), "+f"(d[47])
    : "n"(N) : "memory");
}

__device__ __forceinline__ uint32_t smem_u32(const void* p) { return (uint32_t)__cvta_generic_to_shared(p); }

__device__ __forceinline__ void mbar_init(uint32_t bar, uint32_t cnt) {
  asm volatile("mbarrier.init.shared::cta.b64 [%0], %1;" :: "r"(bar), "r"(cnt) : "memory");
}
__device__ __forceinline__ void mbar_arrive(uint32_t bar) {
  asm volatile("mbarrier.arrive.shared::cta.b64 _, [%0];" :: "r"(bar) : "memory");
}
__device__ __forceinline__ void mbar_wait(uint32_t bar, uint32_t parity) {
  asm volatile("{\n.reg .pred p;\n.reg .u32 n;\n"
               "mov.u32 n, 0;\n"
               "WAIT_LOOP:\n"
               "mbarrier.try_wait.parity.shared::cta.b64 p, [%0], %1;\n"
               "@p bra.uni WAIT_DONE;\n"
               "add.u32 n, n, 1;\n"
               "setp.lt.u32 p, n, 0x1000000;\n"
               "@p bra.uni WAIT_LOOP;\n"
               "trap;\n"
               "WAIT_DONE:\n}\n"
               :: "r"(bar), "r"(parity) : "memory");
}
__device__ __forceinline__ uint32_t mbar_test(uint32_t bar, uint32_t parity) {
  uint32_t ok;
  asm volatile("{\n.reg .pred p;\nmbarrier.test_wait.parity.shared::cta.b64 p, [%1], %2;\nselp.u32 %0, 1, 0, p;\n}\n"
               : "=r"(ok) : "r"(bar), "r"(parity) : "memory");
  return ok;
}
__device__ __forceinline__ void cp_async16(uint32_t dst, const void* src) {
  asm volatile("cp.async.cg.shared.global [%0], [%1], 16;" :: "r"(dst), "l"(src) : "memory");
}
template<int T, int I, bool Z>
__device__ __forceinline__ void cp_row(uint32_t dst, uint64_t& a, uint32_t rows4, uint32_t base, int left, uint64_t pol) {
#define DIN_ADDR "mov.b64 {x, y}, %0;\ndp4a.u32.u32 x, %2, %8, %5;\nmov.b64 %0, {x, y};\n"
  if (Z)
    asm volatile("{\n.reg .u32 x, y;\n.reg .pred p;\n" DIN_ADDR "setp.le.s32 p, %6, %7;\n"
                 "cp.async.cg.shared.global.L2::cache_hint [%1 + %4], [%0], 16, p, %3;\n}\n"
                 : "+l"(a) : "r"(dst), "r"(rows4), "l"(pol), "n"(T * 2048), "r"(base), "r"(left), "n"(T * 16 + I), "n"(0x80u << 8 * I) : "memory");
  else
    asm volatile("{\n.reg .u32 x, y;\n" DIN_ADDR
                 "cp.async.cg.shared.global.L2::cache_hint [%1 + %4], [%0], 16, %3;\n}\n"
                 : "+l"(a) : "r"(dst), "r"(rows4), "l"(pol), "n"(T * 2048), "r"(base), "r"(left), "n"(T * 16 + I), "n"(0x80u << 8 * I) : "memory");
}
template<int T, bool Z>
__device__ __forceinline__ void cp_group(const uint32_t (&dst)[4], uint64_t& a, uint32_t rows4, uint32_t base, int left, uint64_t pol) {
  cp_row<T, 0, Z>(dst[0], a, rows4, base, left, pol);
  cp_row<T, 1, Z>(dst[1], a, rows4, base, left, pol);
  cp_row<T, 2, Z>(dst[2], a, rows4, base, left, pol);
  cp_row<T, 3, Z>(dst[3], a, rows4, base, left, pol);
}
__device__ __forceinline__ uint32_t prmt(uint32_t a, uint32_t b, uint32_t sel) {
  uint32_t d;
  asm("prmt.b32 %0, %1, %2, %3;" : "=r"(d) : "r"(a), "r"(b), "r"(sel));
  return d;
}
__device__ __forceinline__ uint32_t ballot_bit(uint32_t x, uint32_t bit) {
  uint32_t d;
  asm volatile("{\n.reg .pred p;\n.reg .u32 t;\nand.b32 t, %1, %2;\nsetp.ne.u32 p, t, 0;\nvote.sync.ballot.b32 %0, p, 0xffffffff;\n}\n"
               : "=r"(d) : "r"(x), "r"(bit));
  return d;
}
__device__ __forceinline__ uint4 load_mask(const void* mask, uint32_t b, uint32_t i) {
  uint4 m;
  asm volatile("ld.global.nc.L1::no_allocate.v4.u32 {%0,%1,%2,%3}, [%4];"
               : "=r"(m.x), "=r"(m.y), "=r"(m.z), "=r"(m.w) : "l"(reinterpret_cast<const uint4*>(mask) + (b * 25u + i)));
  return m;
}
__device__ __forceinline__ uint32_t nonzero_as_one(uint32_t x) {
  uint32_t d;
  asm("set.neu.bf16x2.bf16x2 %0, %1, %2;" : "=r"(d) : "r"(x), "r"(0u));
  return d;
}
__device__ __forceinline__ void cp_async_arrive_noinc(uint32_t bar) {
  asm volatile("cp.async.mbarrier.arrive.noinc.shared::cta.b64 [%0];" :: "r"(bar) : "memory");
}
__device__ __forceinline__ void ldsm_x4(uint32_t addr, uint32_t& r0, uint32_t& r1, uint32_t& r2, uint32_t& r3) {
  asm volatile("ldmatrix.sync.aligned.m8n8.x4.shared.b16 {%0,%1,%2,%3}, [%4];"
               : "=r"(r0), "=r"(r1), "=r"(r2), "=r"(r3) : "r"(addr) : "memory");
}
__device__ __forceinline__ void ldsm_x4_t(uint32_t addr, uint32_t& r0, uint32_t& r1, uint32_t& r2, uint32_t& r3) {
  asm volatile("ldmatrix.sync.aligned.m8n8.x4.trans.shared.b16 {%0,%1,%2,%3}, [%4];"
               : "=r"(r0), "=r"(r1), "=r"(r2), "=r"(r3) : "r"(addr) : "memory");
}
__device__ __forceinline__ void stsm_x4_t(uint32_t addr, uint32_t r0, uint32_t r1, uint32_t r2, uint32_t r3) {
  asm volatile("stmatrix.sync.aligned.m8n8.x4.trans.shared.b16 [%0], {%1,%2,%3,%4};"
               :: "r"(addr), "r"(r0), "r"(r1), "r"(r2), "r"(r3) : "memory");
}
__device__ __forceinline__ uint32_t hfma2_bf16(uint32_t a, uint32_t b, uint32_t c) {
  uint32_t d;
  asm volatile("fma.rn.bf16x2 %0, %1, %2, %3;" : "=r"(d) : "r"(a), "r"(b), "r"(c));
  return d;
}
__device__ __forceinline__ uint32_t pack_bf16(float lo, float hi) {
  uint32_t d;
  asm("cvt.rn.bf16x2.f32 %0, %1, %2;" : "=r"(d) : "f"(hi), "f"(lo));
  return d;
}
__device__ __forceinline__ uint32_t lds32(uint32_t a) {
  uint32_t v; asm volatile("ld.shared.u32 %0, [%1];" : "=r"(v) : "r"(a) : "memory"); return v;
}
__device__ __forceinline__ uint32_t lds16(uint32_t a) {
  uint32_t v; asm volatile("ld.shared.u16 %0, [%1];" : "=r"(v) : "r"(a) : "memory"); return v;
}
__device__ __forceinline__ void sts32(uint32_t a, uint32_t v) {
  asm volatile("st.shared.u32 [%0], %1;" :: "r"(a), "r"(v) : "memory");
}
__device__ __forceinline__ void sts16(uint32_t a, uint32_t v) {
  asm volatile("st.shared.u16 [%0], %1;" :: "r"(a), "h"((unsigned short)v) : "memory");
}
__device__ __forceinline__ void sts8(uint32_t a, uint32_t v) {
  asm volatile("st.shared.u8 [%0], %1;" :: "r"(a), "r"(v) : "memory");
}
constexpr uint32_t DESC_ROWS = 0x40000040u, DESC_HALVES = 0x80000020u;
__device__ __forceinline__ uint32_t desc_lo(uint32_t addr) { return ((addr & 0x3FFFF) >> 4) | (1u << 16); }

__device__ __forceinline__ uint4 lds128(uint32_t a) {
  uint4 v;
  asm volatile("ld.shared.v4.u32 {%0,%1,%2,%3}, [%4];" : "=r"(v.x), "=r"(v.y), "=r"(v.z), "=r"(v.w) : "r"(a) : "memory");
  return v;
}
__device__ __forceinline__ void sts128(uint32_t a, uint4 v) {
  asm volatile("st.shared.v4.u32 [%0], {%1,%2,%3,%4};" :: "r"(a), "r"(v.x), "r"(v.y), "r"(v.z), "r"(v.w) : "memory");
}
__device__ __forceinline__ void prefetch_l2(const void* p, uint32_t bytes) {
  asm volatile("cp.async.bulk.prefetch.L2.global [%0], %1;" :: "l"(p), "r"(bytes) : "memory");
}

__device__ __forceinline__ void cut_here(uint32_t& any, uint32_t zero) {
  asm volatile("{\n.reg .pred p;\nsetp.ne.u32 p, %1, 0;\n@p mov.u32 %0, %%clock;\n}\n" : "+r"(any) : "r"(zero) : "memory");
}
__device__ __forceinline__ void mma_fence() { asm volatile("wgmma.fence.sync.aligned;" ::: "memory"); }
__device__ __forceinline__ void mma_commit() { asm volatile("wgmma.commit_group.sync.aligned;" ::: "memory"); }
template<bool FIRST>
__device__ __forceinline__ void hmma(float (&c)[4], const uint32_t* a, uint32_t b0, uint32_t b1) {
  if (FIRST)
    asm volatile("mma.sync.aligned.m16n8k16.row.col.f32.bf16.bf16.f32 {%0,%1,%2,%3}, {%4,%5,%6,%7}, {%8,%9}, {%10,%10,%10,%10};"
                 : "=f"(c[0]), "=f"(c[1]), "=f"(c[2]), "=f"(c[3]) : "r"(a[0]), "r"(a[1]), "r"(a[2]), "r"(a[3]), "r"(b0), "r"(b1), "f"(0.f));
  else
    asm volatile("mma.sync.aligned.m16n8k16.row.col.f32.bf16.bf16.f32 {%0,%1,%2,%3}, {%4,%5,%6,%7}, {%8,%9}, {%0,%1,%2,%3};"
                 : "+f"(c[0]), "+f"(c[1]), "+f"(c[2]), "+f"(c[3]) : "r"(a[0]), "r"(a[1]), "r"(a[2]), "r"(a[3]), "r"(b0), "r"(b1));
}
__device__ __forceinline__ void tanh_some(float* d, int i0, int i1) {
#pragma unroll
  for (int i = i0; i < i1; i++) asm volatile("tanh.approx.f32 %0, %0;" : "+f"(d[i ^ 2]));
}
__device__ __forceinline__ uint32_t mix(const float* d, int i, float r) {
  uint32_t p;
  asm volatile("{\n.reg .f32 x, y;\nfma.rn.f32 x, %3, %5, %1;\nfma.rn.f32 y, %4, %5, %2;\ncvt.rn.bf16x2.f32 %0, y, x;\n}\n"
               : "=r"(p) : "f"(d[4 * i]), "f"(d[4 * i + 1]), "f"(d[4 * i + 2]), "f"(d[4 * i + 3]), "f"(r));
  return p;
}
__device__ __forceinline__ uint32_t sums_at(uint32_t d) { return S_OUT + (d ^ ((d >> 3) & 1)) * 16; }
template<int K> __device__ __forceinline__ uint32_t keep(uint32_t x) { return K ? __shfl_sync(0xffffffffu, x, 0) : x; }

template<int PF_M, int PF_T>
__global__ void __launch_bounds__(NTHREADS, 1)
din_kernel(const __nv_bfloat16* __restrict__ mask, const __nv_bfloat16* __restrict__ target, int B, int grid,
           const __nv_bfloat16* __restrict__ w1, const __nv_bfloat16* __restrict__ hist,
           const __nv_bfloat16* __restrict__ b1, const __nv_bfloat16* __restrict__ w2,
           const __nv_bfloat16* __restrict__ b2, __nv_bfloat16* __restrict__ out, unsigned int* counter, int pace16,
           int slow_pace, int slow_from) {
  const uint32_t tid = threadIdx.x, pf_at = blockIdx.x * NTHREADS + tid;
  asm volatile("{\n.reg .pred p;\nprefetch.global.L2 [%0];\nsetp.gt.u32 p, %1, 0x7ffffff0;\n@p exit;\n}\n"
               :: "l"(reinterpret_cast<const char*>(mask) + (size_t)pf_at * PF_M), "r"(blockIdx.x) : "memory");
  asm volatile("prefetch.global.L2 [%0];" :: "l"(reinterpret_cast<const char*>(target) + (size_t)pf_at * PF_T));
  extern __shared__ unsigned char smem_raw[];
  const uint32_t sb = (smem_u32(smem_raw) + 1023u) & ~1023u;
  const int lane = tid & 31;
  const uint32_t gwarp = __shfl_sync(0xffffffffu, pf_at >> 5, 0), cta = gwarp / (NTHREADS / 32);
  const int warp = gwarp % (NTHREADS / 32);
#define ACT NCW
  const int bstep = ACT * grid;

  if (warp < NCW * 4) {
    const int wg = warp >> 2, w = warp & 3;
    const int g = lane >> 2;
    const uint32_t ring = sb + wg * RING_BYTES;
    const bool active = wg * grid + (int)cta < B && wg < ACT;
    {
      const int t = tid & 127;
      const uint32_t dst = sb + ((t ^ ((t >> 3) & 7)) << 4);
      const char* src = reinterpret_cast<const char*>(w1) + t * 16;
#pragma unroll
      for (int i = 0; i < 4; i++) cp_async16(dst + w1_at(i) + wg * 2048, src + i * 8192 + wg * 2048);
      cp_async16(dst + w1_at(0) + wg * 8192 + 6144, src + wg * 8192 + 6144);
      if (wg == 0) cp_async16(dst + w1_at(3) + 6144, src + 3 * 8192 + 6144);
      if (lane < 8) {
        if (w == 0 && active) cp_async16(ring + R_TGT0 + lane * 16, target + (size_t)(wg * grid + cta) * kD + lane * 8);
        if (w == 1 && wg < 2) cp_async16(ring + R_VEC + lane * 16, (wg ? w2 : b1) + lane * 8);
      }
    }
    if (w == 2) sts32(ring + R_SEL + lane * 4, 0x3e803e80u);
    uint32_t rb2;
    asm volatile("ld.global.nc.u16 %0, [%1];" : "=r"(rb2) : "l"(b2));
    asm volatile("setmaxnreg.inc.sync.aligned.u32 %0;" :: "n"(CONS_REGS));
    asm volatile("cp.async.wait_all;" ::: "memory");
    asm volatile("bar.sync 1, %0;" :: "n"(NCW * 160) : "memory");
    float r;
    uint32_t cq, swap, half2, bf[4];
    {
      const uint32_t v2 = sb + RING_BYTES + R_VEC + ((lane & 24) * 2 + (lane & 7)) * 2;
      const float x = __uint_as_float(lds16(v2) << 16), y = __uint_as_float(lds16(v2 + 16) << 16);
      float c = x + y;
#pragma unroll
      for (int o = 16; o; o >>= 1) c += __shfl_xor_sync(0xffffffffu, c, o);
      c = 0.5f * c + __uint_as_float(rb2 << 16);
      const bool sw = fabsf(y) > fabsf(x);
      const float u = sw ? y : x, v = sw ? x : y;
      const bool off = !(fabsf(u) > fabsf(c) * 0x1p-40f);
      const float sc = off ? __uint_as_float(max(__float_as_uint(c) & 0x7f800000u, 8u << 23) - (4u << 23)) : 0.5f * u;
      float upto = fabsf(sc);
#pragma unroll
      for (int o = 2; o < 32; o *= 2) {
        const float z = __shfl_up_sync(0xffffffffu, upto, o);
        if (lane >= o) upto += z;
      }
      const float all = __shfl_sync(0xffffffffu, upto, 30 + (lane & 1));
      const float m = c / all;
      const float grid_ = __uint_as_float((__float_as_uint(2.0625f + 1.03125f * fabsf(m)) & 0x7f800000u) - (7u << 23));
      const float m0 = __fadd_rn(__fadd_rn(m, grid_ * 0x1.8p23f), grid_ * -0x1.8p23f);
      const float rest = fmaf(-m0, all, c);
      float q = (upto - 0.5f * fabsf(sc)) * grid_ < fabsf(rest) ? m0 + copysignf(grid_, rest) : m0;
      if (sc < 0.f) q = -q;
      const int own = 8 * w + g;
      r = __shfl_sync(0xffffffffu, off ? 0.f : v / u, own);
      cq = __shfl_sync(0xffffffffu, pack_bf16(q, q), own);
      swap = __shfl_sync(0xffffffffu, sw, own);
      half2 = __shfl_sync(0xffffffffu, off ? 0u : 0x3f003f00u, own);
      const int odd = (g ^ (g >> 1)) & 1;
#pragma unroll
      for (int i = 0; i < 4; i++)
        bf[i] = (__float_as_uint(__shfl_sync(0xffffffffu, sc, 8 * i + 2 * (lane & 3) + odd)) >> 16) << (16 * odd);
      if (warp == 0) {
        sts128(sb + SCALES + lane * 16, make_uint4(bf[0], bf[1], bf[2], bf[3]));
        asm volatile("bar.arrive 6, 160;" ::: "memory");
      }
    }
    const uint32_t nhalf2 = half2 ^ 0x80008000u, nzero2 = 0x80008000u;
    const uint32_t vec = sb + R_VEC + (16 * w + g) * 2;
    const float b1a = __uint_as_float(half2 << 16) * __uint_as_float(lds16(vec + (swap ? 16 : 0)) << 16);
    const float b1b = __uint_as_float(half2 << 16) * __uint_as_float(lds16(vec + (swap ? 0 : 16)) << 16);
    uint32_t wac[16], wd[16], wbc[16];
    {
      const int mi = lane >> 3, rr = lane & 7;
      const uint32_t a0 = sb + (8 * (mi >> 1) + rr) * 128 + (((2 * w + (mi & 1)) ^ rr) << 4);
#pragma unroll
      for (int ks = 0; ks < 4; ks++) {
        uint32_t A[4], Bm[4], C[4], Dm[4];
        ldsm_x4_t(a0 + ks * 2048 + w1_at(0), A[0], A[1], A[2], A[3]);
        ldsm_x4_t(a0 + ks * 2048 + w1_at(1), Bm[0], Bm[1], Bm[2], Bm[3]);
        ldsm_x4_t(a0 + ks * 2048 + w1_at(2), C[0], C[1], C[2], C[3]);
        ldsm_x4_t(a0 + ks * 2048 + w1_at(3), Dm[0], Dm[1], Dm[2], Dm[3]);
#pragma unroll
        for (int e = 0; e < 4; e++) {
          A[e] = hfma2_bf16(A[e], half2, hfma2_bf16(C[e], half2, nzero2));
          Bm[e] = hfma2_bf16(Bm[e], half2, hfma2_bf16(C[e], nhalf2, nzero2));
          Dm[e] = hfma2_bf16(Dm[e], half2, nzero2);
        }
#pragma unroll
        for (int e = 0; e < 4; e++) {
          wac[4 * ks + e] = swap ? A[e ^ 1] : A[e];
          wbc[4 * ks + e] = swap ? Bm[e ^ 1] : Bm[e];
          wd[4 * ks + e] = swap ? Dm[e ^ 1] : Dm[e];
        }
      }
    }
    asm volatile("fence.proxy.async.shared::cta;" ::: "memory");
    asm volatile("bar.sync 5, %0;" :: "n"(NCW * 128) : "memory");

    const uint32_t ln = __shfl_sync(0xffffffffu, lane, lane);
    const uint32_t meta = __shfl_sync(0xffffffffu, g & 1 ? 0xdd8888ddu : 0x88dddd88u, lane);
    const uint32_t zr = grid >> 20;
    const uint32_t sel = keep<K_SEL>(((ring + R_SEL) & 0x3FFFF) >> 4);
    const uint32_t rat = __shfl_sync(0xffffffffu, sums_at(8 * w + (lane & 7)) + (lane >> 3) * 512, lane);
    const uint32_t barid = __shfl_sync(0xffffffffu, 2 + (tid >> 7), lane);
    const uint32_t toff = __shfl_sync(0xffffffffu, (lane & 24) << 1, lane);
    const uint32_t ost = __shfl_sync(0xffffffffu, w * 1024 + sums_at(lane), lane);
    if (active) {
      uint32_t t[8];
      auto load_t = [&](uint32_t ta) {
        ldsm_x4(ta + toff, t[0], t[1], t[2], t[3]);
        ldsm_x4(ta + toff + 64, t[4], t[5], t[6], t[7]);
      };
      load_t(ring + R_TGT0);
      uint32_t hdr = keep<1>(ring), raw, cur = hdr + (R_START - S_EMPTY);
      uint32_t x, nxt;
      auto peek_header = [&]() {
        nxt = hdr & H_NEXT;
        if (K_NX == 1) asm volatile("" : "+r"(nxt));
        x = lds32(nxt + S_HDR);
      };
      auto next_header = [&]() {
        asm volatile("{\n.reg .pred p;\n.reg .u32 n;\n.reg .s32 y;\n"
                     "xor.b32 y, %0, %2;\nsetp.ge.s32 p, y, 0;\n@p bra.uni FRESH;\n"
                     "mov.u32 n, 0;\n"
                     "AGAIN:\nadd.u32 n, n, 1;\nsetp.gt.u32 p, n, 0x1000000;\n@p trap;\nnanosleep.u32 32;\n"
                     "ld.shared.u32 %0, [%1];\nxor.b32 y, %0, %2;\nsetp.lt.s32 p, y, 0;\n@p bra.uni AGAIN;\n"
                     "FRESH:\n}\n" : "+r"(x) : "r"(nxt + S_HDR), "r"(hdr << 1) : "memory");
        if (!K_TOP) raw = __shfl_sync(0xffffffffu, x, 0);
      };
      peek_header();
      next_header();
      while (true) {
        __syncwarp();
        if (ln == 0) mbar_arrive(cur + S_EMPTY);
        cur = K_NX == 2 ? hdr & H_NEXT : nxt;
        hdr = K_TOP ? __shfl_sync(0xffffffffu, x, 0) : raw;
        uint32_t we[16], bq[4];
        {
          float c[4][4];
          asm volatile("mma.sync.aligned.m16n8k16.row.col.f32.bf16.bf16.f32 {%0,%1,%2,%3}, {%4,%5,%6,%7}, {%8,%9}, {%10,%11,%12,%13};"
                       : "=f"(c[0][0]), "=f"(c[0][1]), "=f"(c[0][2]), "=f"(c[0][3])
                       : "r"(wbc[0]), "r"(wbc[1]), "r"(wbc[2]), "r"(wbc[3]), "r"(t[0]), "r"(t[1]), "f"(b1a), "f"(r), "f"(b1b), "f"(__uint_as_float(cq)));
#pragma unroll
          for (int i = 1; i < 4; i++) hmma<true>(c[i], wbc + 4 * i, t[2 * i], t[2 * i + 1]);
#pragma unroll
          for (int i = 0; i < 16; i++) we[i] = hfma2_bf16(t[i >> 1], wd[i], wac[i]);
#pragma unroll
          for (int i = 0; i < 4; i++) bq[i] = pack_bf16(c[i & 2][2 * (i & 1)], c[(i & 2) + 1][2 * (i & 1)]);
        }
        auto chunk = [&](auto groups) {
          constexpr int N8 = decltype(groups)::value, KE = (N8 + 1) / 2, KA = KE - KL;
          float d[4 * N8], o[16];
          uint32_t a[4 * KE];
          auto scores = [&](int i0, int i1) {
#pragma unroll
            for (int i = i0; i < i1; i++) {
              a[2 * i] = i < N8 ? mix(d, i, r) : 0;
              a[2 * i + 1] = i < N8 ? hfma2_bf16(a[2 * i], 0x3f803f80u, cq) : 0;
              if (N8 == 16) {
                uint32_t m = 0x3f803f80u;
                asm volatile("{\n.reg .pred p;\nsetp.ne.u32 p, %1, 0;\n@p ld.shared.u32 %0, [%2];\n}\n"
                             : "+r"(m) : "r"(hdr & H_GENERAL), "r"(cur + S_MASK + i * 16 + (ln & 3) * 4) : "memory");
                a[2 * i] = hfma2_bf16(a[2 * i], m, 0x80008000u);
                a[2 * i + 1] = hfma2_bf16(a[2 * i + 1], m, 0x80008000u);
              }
            }
          };
          const uint32_t lo = cur >> 4, lo1 = lo + 0x10000, lo2 = lo + K_LO2 * 0x10000;
          const uint32_t hi1 = DESC_ROWS + (K_HI1 == 1 ? cur >> 24 : lo >> 19);
          const uint32_t hi2 = K_HI2 == 1 ? DESC_HALVES + (cur >> 24) : hi1 + (DESC_HALVES - DESC_ROWS);
          auto g2 = [&](int k) {
            if (k == 0) g2_first(o, a, lo2, meta, hi2); else g2_more(o, a + 4 * k, lo2 + 128 * k, meta, hi2);
          };
          uint32_t oa = cur + ost;
          mma_fence();
          g1_bias<NA>(d, bq, sel);
          g1_bias<N8 - NA>(d + 4 * NA, bq, sel);
          mma_commit();
          mbar_wait(cur + S_FULL, hdr >> 31);
          mma_fence();
#pragma unroll
          for (int k = 0; k < 4; k++) g1_step<NA>(d, we + 4 * k, lo1 + 2 * k, hi1);
          mma_commit();
#pragma unroll
          for (int k = 0; k < 4; k++) g1_step<N8 - NA>(d + 4 * NA, we + 4 * k, lo1 + 64 * NA + 2 * k, hi1);
          mma_commit();
          mma_wait<1>(d, Int<NA>());
          tanh_some(d, 0, 4 * NA);
          scores(0, S0);
          cut_here(oa, zr);
          mma_wait<0>(d + 4 * NA, Int<N8 - NA>());
          load_t(cur + S_TGT);
          peek_header();
          tanh_some(d, 4 * NA, 8 * KA + D0);
          scores(S0, 2 * KA);
          mma_fence();
#pragma unroll
          for (int k = 0; k < KA; k++) {
            g2(k);
            if (k == KA - KC) cut_here(oa, zr);
          }
          mma_commit();
          tanh_some(d, 8 * KA + D0, 4 * N8);
          scores(2 * KA, 2 * KE);
          mma_fence();
#pragma unroll
          for (int k = KA; k < KE; k++) g2(k);
          mma_commit();
          next_header();
          mma_wait<0>(o, Int<4>());
#pragma unroll
          for (int e = 0; e < 2; e++)
            stsm_x4_t(oa + e * 512, pack_bf16(o[2 * e], o[2 * e + 1]), pack_bf16(o[2 * e + 4], o[2 * e + 5]),
                      pack_bf16(o[2 * e + 8], o[2 * e + 9]), pack_bf16(o[2 * e + 12], o[2 * e + 13]));
        };
        if (hdr & H_13) { chunk(Int<13>()); if (hdr & (H_FINAL | H_12)) break; }
        else if (hdr & H_12) { chunk(Int<12>()); if (hdr & (H_FINAL | H_14)) break; }
        else if (hdr & H_14) { chunk(Int<14>()); if (hdr & (H_FINAL | H_15)) break; }
        else if (hdr & H_15) { chunk(Int<15>()); if (hdr & (H_FINAL | H_16)) break; }
        else { chunk(Int<16>()); if (hdr & H_FINAL) break; }
      }
      asm volatile("bar.sync %0, 128;" :: "r"(K_BAR ? barid : 2 + wg) : "memory");
      uint32_t u[8], l2 = ln;
      ldsm_x4(cur + rat, u[0], u[1], u[2], u[3]);
      ldsm_x4(cur + rat + 2048, u[4], u[5], u[6], u[7]);
      cut_here(l2, zr);
      __nv_bfloat16* dst = out + (x * kD + 8 * w + (l2 >> 2) + (l2 & 1) * 32);
      asm volatile("" : "+l"(dst));
      cut_here(l2, zr);
      float c[4], e[4];
      hmma<true>(c, u, bf[0], bf[1]);
      hmma<true>(e, u + 4, bf[2], bf[3]);
      asm volatile("{\n.reg .pred p, q;\nsetp.eq.u32 q, %3, 0;\nsetp.eq.and.u32 p, %2, 0, q;\n"
                   "@p mbarrier.arrive.shared::cta.b64 _, [%1];\n@q exit;\n}\n"
                   : "+l"(dst) : "r"(cur + S_EMPTY), "r"(l2), "r"(hdr & H_SELF) : "memory");
      asm volatile("st.global.u16 [%0], %1;"
                   :: "l"(dst), "h"(__bfloat16_as_ushort(__float2bfloat16((c[0] + c[3]) + (e[0] + e[3])))) : "memory");
      asm volatile("exit;");
    }
  } else {
    const int pw = warp - NCW * 4;
    const uint32_t ring = sb + pw * RING_BYTES;
    asm volatile("setmaxnreg.dec.sync.aligned.u32 %0;" :: "n"(PROD_REGS));
    if (pw < NCW) {
      int b = pw * grid + cta, bn = b + bstep;
      uint4 mw = load_mask(mask, min(b, B - 1), min(lane, 24));
      if (lane == 0) {
#pragma unroll
        for (int i = 0; i < NSLOT; i++) {
          mbar_init(ring + i * SLOT_BYTES + S_FULL, 34);
          mbar_init(ring + i * SLOT_BYTES + S_EMPTY, 4);
          mbar_arrive(ring + i * SLOT_BYTES + S_FULL);
          sts32(ring + i * SLOT_BYTES + S_HDR, 0x80000000u);
        }
        mbar_init(ring + R_START, 4);
        sts32(ring + R_STOP, pw < ACT ? 0 : ring);
      }
      sts32(sb + R_PACE + lane * 4, 0);
      asm volatile("bar.arrive 1, %0;" :: "n"(NCW * 160) : "memory");
      asm volatile("bar.arrive 6, 160;" ::: "memory");
      if (pw >= ACT) return;
      const uint32_t list = ring + R_LIST;
      uint32_t lt;
      asm("mov.u32 %0, %%lanemask_lt;" : "=r"(lt));
      const uint32_t ln = __shfl_sync(0xffffffffu, lane, lane);
      const uint32_t r4 = (ln >> 3) * 4, c16 = (ln & 7) * 16, l25 = min(ln, 24u);
      const uint32_t pick = ln < 25 ? 0xeca8 : 0x9999;
      uint32_t dst[4];
#pragma unroll
      for (int i = 0; i < 4; i++) dst[i] = ring + (r4 + i) * 128 + (c16 ^ (((r4 + i) & 7) << 4));
      uint64_t pol;
      asm("createpolicy.fractional.L2::evict_first.b64 %0, 1.0;" : "=l"(pol));
      uint32_t sa = ring, phase = 1;
      const uint32_t wrap = (uint32_t)(max(B - NSTATIC * bstep, 0) + bstep - 1);
      auto next_slot = [&]() {
        const bool wrapped = sa == ring + (NSLOT - 1) * SLOT_BYTES;
        const int step = wrapped ? -(NSLOT - 1) * SLOT_BYTES : SLOT_BYTES;
        sa += step;
        phase ^= wrapped;
#pragma unroll
        for (int i = 0; i < 4; i++) dst[i] += step;
      };
      uint32_t claimer = ln;
      uint32_t drawn;
      auto draw = [&]() {
        drawn = B;
        asm volatile("{\n.reg .pred p;\nsetp.eq.u32 p, %3, 0;\n@p atom.global.inc.u32 %0, [%1], %2;\n}\n"
                     : "+r"(drawn) : "l"(counter), "r"(wrap), "r"(claimer) : "memory");
      };
      if (b >= B) draw();
      int n = kL, mean16 = 8 * kL;
      while (b < B) {
        const uint32_t e0 = nonzero_as_one(mw.x), e1 = nonzero_as_one(mw.y);
        const uint32_t e2 = nonzero_as_one(mw.z), e3 = nonzero_as_one(mw.w);
        const uint32_t nonbin = (e0 ^ mw.x) | (e1 ^ mw.y) | (e2 ^ mw.z) | (e3 ^ mw.w);
        const uint32_t sA = prmt(e0, e1, pick), sB = prmt(e2, e3, pick);
        const uint32_t pA = (sA & 0x01010101u) * 0x01010101u;
        const uint32_t pB = ((sB & 0x01010101u) + (pA >> 24)) * 0x01010101u;
        uint32_t pos = 0;
        n = 0;
#pragma unroll
        for (int k = 0; k < 4; k++) {
          const uint32_t bal = ballot_bit(pB, 0x01000000u << k);
          pos += __popc(bal & lt) << k;
          n += __popc(bal) << k;
        }
        const uint32_t general = __any_sync(0xffffffffu, nonbin != 0);
        const uint32_t aA = (pA + pos * 0x01010101u) | ~sA, aB = (pB + pos * 0x01010101u) | ~sB;
#pragma unroll
        for (int i = 0; i < 8; i++) sts8(list - 1 + prmt(i < 4 ? aA : aB, 0, 0x4440 + (i & 3)), 8 * ln + i);
        __syncwarp();

        const uint64_t src = reinterpret_cast<uint64_t>(hist) + (uint64_t)b * (kL * kD * 2);
        const bool no_carry = (uint32_t)src <= 0xffffffffu - kL * kD * 2;
        auto begin_fill = [&](uint32_t h, uint32_t part, int nc, int bt, auto extra) {
          mbar_wait(sa + S_EMPTY, phase);
          if (bt >= B) h |= part ? H_FINAL : H_FINAL | H_SELF;
          extra();
          {
            const bool wrapped = sa == ring + (NSLOT - 1) * SLOT_BYTES;
            sts32(sa + S_HDR, (h | (wrapped ? ring + 0x40000000u : sa + SLOT_BYTES)) ^ ((phase - 1) & 0xc0000000u));
          }
          sts32(sa + S_ROW + phase * 4, b | part);
          asm volatile("{\n.reg .pred p;\nsetp.eq.u32 p, %1, 0;\n@p mbarrier.arrive.shared::cta.b64 _, [%0];\n}\n"
                       :: "r"(sa + S_FULL), "r"(ln) : "memory");
          mean16 += nc - (mean16 >> 4);
          asm volatile("{\n.reg .u32 f, c;\n.reg .s32 d;\n.reg .pred p;\n"
                       "mov.u32 c, %%globaltimer_lo;\n"
                       "red.shared.max.u32 [%0], c;\n"
                       "atom.shared.add.u32 f, [%0], %1;\n"
                       "shfl.sync.idx.b32 f, f, 0, 31, 0xffffffff;\n"
                       "SPIN:\n"
                       "mov.u32 c, %%globaltimer_lo;\n"
                       "sub.s32 d, c, f;\n"
                       "setp.gt.u32 p, d, %2;\n"
                       "@p bra.uni SPIN;\n}\n" :: "r"(sb + R_PACE + ln * 4), "r"((bn >= slow_from ? mean16 * slow_pace : nc * pace16) >> 8), "r"(~(pace16 * (CHUNK / 64))) : "memory");
          if (!(part & ROW_REST)) {
            mw = load_mask(mask, min(bn, B - 1), l25);
            draw();
          }
          asm volatile("cp.async.ca.shared.global [%0], [%1], 4;"
                       :: "r"(sa + S_TGT + ln * 4), "l"(reinterpret_cast<const uint32_t*>(target) + ((uint32_t)min(bt, B - 1) * 32u + ln)) : "memory");
        };
        auto end_fill = [&](int nc) {
          cp_async_arrive_noinc(sa + S_FULL);
          next_slot();
        };
        auto usual = [&]() {
          uint32_t idx[7];
#pragma unroll
          for (int t = 0; t < 7; t++) idx[t] = lds32(list + r4 + t * 16);
          begin_fill(size_flag(n), 0, n, bn, [](){});
          const int left = n - r4;
          const uint32_t base = (uint32_t)src + c16;
          uint64_t a = (uint64_t)((uint32_t)(src >> 32) + (ln >> 5)) << 32;
          cp_group<0, false>(dst, a, idx[0], base, left, pol);
          cp_group<1, false>(dst, a, idx[1], base, left, pol);
          cp_group<2, false>(dst, a, idx[2], base, left, pol);
          cp_group<3, false>(dst, a, idx[3], base, left, pol);
          cp_group<4, true>(dst, a, idx[4], base, left, pol);
          cp_group<5, true>(dst, a, idx[5], base, left, pol);
          if (n > 96) {
            cp_group<6, true>(dst, a, idx[6], base, left, pol);
            if (n > 112) cp_group<7, true>(dst, a, lds32(list + r4 + 112), base, left, pol);
          }
          end_fill(n);
        };
        auto other = [&]() {
          int r0 = 0, nc = n <= CHUNK ? n : n <= 160 ? 64 : 96;
#pragma unroll 1
          do {
            const bool more = r0 + nc < n;
            begin_fill(general ? H_GENERAL : size_flag(max(nc, 64)), (more ? ROW_MORE : 0u) | (r0 ? ROW_REST : 0u), nc, more ? b : bn, [&]() {
#pragma unroll 1
              for (int z = ln; general && z < CHUNK; z += 32) {
                uint32_t v = 0;
                if (z < nc) {
                  uint32_t row;
                  asm volatile("ld.shared.u8 %0, [%1];" : "=r"(row) : "r"(list + r0 + z) : "memory");
                  v = __bfloat16_as_ushort(mask[(size_t)b * kL + row]);
                }
                sts16(sa + S_MASK + z * 2, v);
              }
              __syncwarp();
            });
            uint32_t rows4 = lds32(list + r0 + r4);
#pragma unroll 1
            for (int z = 0; z < CHUNK; z += 16) {
              const uint32_t now = rows4;
              rows4 = lds32(list + r0 + r4 + z + 16);
#pragma unroll
              for (int i = 0; i < 4; i++)
                asm volatile("{\n.reg .pred p;\nsetp.ge.s32 p, %2, %3;\ncp.async.cg.shared.global [%0], [%1], 16, p;\n}\n"
                             :: "r"(dst[i] + z * 128), "l"(src + c16 + prmt(now, 0, 0x4440 + i) * 128), "r"(z + r4 + i), "r"(nc) : "memory");
            }
            end_fill(nc);
            r0 += nc;
            nc = n - nc;
          } while (r0 < n);
        };
        if (n < 64 || n > CHUNK || !no_carry || general) other(); else usual();
        if (bn >= B) break;
        b = bn;
        bn = __shfl_sync(0xffffffffu, drawn, 0) + NSTATIC * bstep;
        if (bn >= B) claimer = 1;
      }
      if (b < B) mbar_wait(ring + R_START, 0);
      sts32(sa + S_HDR, b | (phase ^ 1) << 31);
      if (n <= CHUNK) {
#pragma unroll 1
        for (int i = 1; i < 2 * NSLOT; i++) next_slot();
      }
      sts32(ring + R_STOP, sa + (phase ^ 1));
      asm volatile("cp.async.wait_all;" ::: "memory");
    } else {
      uint32_t due = clock();
      int s0 = NSTATIC * bstep + (PF_EARLY * grid + cta) * PF_ROWS;
      auto prefetch = [&]() {
        const int cnt = min(PF_ROWS, B - s0);
        if (lane == 0) {
          prefetch_l2(mask + (size_t)s0 * kL, cnt * kL * 2);
          prefetch_l2(target + (size_t)s0 * kD, cnt * kD * 2);
        }
        s0 += grid * PF_ROWS;
      };
#pragma unroll 1
      for (int j = PF_EARLY; j < PF_FAST && s0 < B; j++) {
        while ((int)(due - (uint32_t)clock()) > 0) {}
        prefetch();
        due += PF_CYCLES;
      }
      due += (PF_FAST - 1) * PF_SLOW - (PF_FAST - PF_EARLY) * PF_CYCLES + (cta & 255) * (PF_SLOW / 256);
      asm volatile("bar.sync 6, 160;" ::: "memory");
      constexpr uint32_t WHERE = 0x3ffff;
      const uint32_t mine = __shfl_sync(0xffffffffu, sb + min(lane, NCW - 1) * RING_BYTES, lane);
      uint32_t at = mine | ~WHERE;
      const uint32_t ln = __shfl_sync(0xffffffffu, lane, lane);
      const uint32_t rd = __shfl_sync(0xffffffffu, sums_at(2 * (lane & 7)) + (lane >> 3) * 512, lane);
      uint4 bf = lds128(sb + SCALES + lane * 16);
      bf.x += grid >> 20;
      bf.z += grid >> 20;
      uint32_t* const dst = reinterpret_cast<uint32_t*>(out) + ((lane & 1) * 16 + (lane & 2) * 4 + (lane >> 2));
      uint32_t idle = 0;
#pragma unroll 1
      while (true) {
        const uint32_t go = __reduce_max_sync(0xffffffffu, mbar_test((at & (WHERE - 1)) + S_EMPTY, at & 1) ? at : 0u);
        if (go) {
          const uint32_t sa = go & (WHERE - 1);
          const uint32_t row = lds32(sa + S_ROW + 4 - (go & 1) * 4);
          uint32_t u[8][4];
#pragma unroll
          for (int i = 0; i < 8; i++) ldsm_x4(((sa + rd) ^ (i & 1) * 16) + (i & 2) * 128 + (i >> 2) * 2048, u[i][0], u[i][1], u[i][2], u[i][3]);
          cut_here(idle, sa == 0);
          float c[4][4];
#pragma unroll
          for (int j = 0; j < 4; j++) hmma<true>(c[j], u[j], bf.x, bf.y);
#pragma unroll
          for (int j = 0; j < 4; j++) hmma<false>(c[j], u[4 + j], bf.z, bf.w);
          float e0 = c[0][0] + c[0][3], e1 = c[1][0] + c[1][3];
          if (ln & 2) { e0 = c[2][0] + c[2][3]; e1 = c[3][0] + c[3][3]; }
          __syncwarp();
          if (ln == 0) mbar_arrive(sa + S_FULL);
          if (at == go) at = (sa == mine + (NSLOT - 1) * SLOT_BYTES ? (at - (NSLOT - 1) * SLOT_BYTES) ^ 1 : at + SLOT_BYTES) - (WHERE + 1);
          if (__builtin_expect(row >= ROW_REST, 0)) {
            const uint32_t carry = __reduce_max_sync(0xffffffffu, mine <= sa ? mine : 0u) + R_CARRY + ln * 8;
            if (row & ROW_REST) { e0 += __uint_as_float(lds32(carry)); e1 += __uint_as_float(lds32(carry + 4)); }
            sts32(carry, __float_as_uint(e0));
            sts32(carry + 4, __float_as_uint(e1));
          }
          if (row < ROW_MORE) dst[(row & (ROW_REST - 1)) * 32] = pack_bf16(e0, e1);
        } else {
          if (__all_sync(0xffffffffu, lds32(mine + R_STOP) == (at & WHERE))) break;
          if (++idle > 0x4000000) __trap();
          if (s0 < B && (int)(due - (uint32_t)clock()) <= 0) { prefetch(); due += PF_SLOW; }
          if (RED_SLEEP) __nanosleep(RED_SLEEP);
        }
      }
    }
  }
}

}

extern "C" void kernel_launch(void* const* d_in, const int* in_sizes, int n_in, void* d_out, int out_size) {
  const __nv_bfloat16* target = (const __nv_bfloat16*)d_in[0];
  const __nv_bfloat16* hist = (const __nv_bfloat16*)d_in[1];
  const __nv_bfloat16* mask = (const __nv_bfloat16*)d_in[2];
  const __nv_bfloat16* w1 = (const __nv_bfloat16*)d_in[3];
  const __nv_bfloat16* b1 = (const __nv_bfloat16*)d_in[4];
  const __nv_bfloat16* w2 = (const __nv_bfloat16*)d_in[5];
  const __nv_bfloat16* b2 = (const __nv_bfloat16*)d_in[6];
  const int B = in_sizes[0] / din::kD;
  if (B <= 0) return;
  constexpr int early_rows = din::NSTATIC * NCW + PF_EARLY * PF_ROWS;
  constexpr int pf_mask = (early_rows * din::kL * 2 + din::NTHREADS - 1) / din::NTHREADS;
  constexpr int pf_tgt = (early_rows * din::kD * 2 + din::NTHREADS - 1) / din::NTHREADS;
  static int sms = 0, pace = 0;
  static unsigned int* counter = nullptr;
  if (sms == 0) {
    int dev = 0, khz = 0, bits = 0;
    cudaGetDevice(&dev);
    cudaDeviceGetAttribute(&sms, cudaDevAttrMultiProcessorCount, dev);
    cudaDeviceGetAttribute(&khz, cudaDevAttrMemoryClockRate, dev);
    cudaDeviceGetAttribute(&bits, cudaDevAttrGlobalMemoryBusWidth, dev);
    if (khz > 0 && bits > 0) pace = (int)(16.0 * 128.0 * sms / (khz * 1e-6 * 2.0 * bits / 8.0));
    if (pace > 256) pace = 0;
    cudaGetSymbolAddress((void**)&counter, din::g_next);
    cudaFuncSetAttribute(din::din_kernel<0, 0>, cudaFuncAttributeMaxDynamicSharedMemorySize, din::SMEM_BYTES);
    cudaFuncSetAttribute(din::din_kernel<pf_mask, pf_tgt>, cudaFuncAttributeMaxDynamicSharedMemorySize, din::SMEM_BYTES);
  }
  const bool early = (long long)pf_mask * din::NTHREADS * sms <= (long long)B * din::kL * 2 &&
                     (long long)pf_tgt * din::NTHREADS * sms <= (long long)B * din::kD * 2;
  (early ? din::din_kernel<pf_mask, pf_tgt> : din::din_kernel<0, 0>)<<<sms, din::NTHREADS, din::SMEM_BYTES>>>(
      mask, target, B, sms, w1, hist, b1, w2, b2, (__nv_bfloat16*)d_out, counter, pace * 16,
      pace + pace * SLOW_BY / 80, B - SLOW_ROUNDS * NCW * sms);
}
```

```cpp
#include <cuda_runtime.h>
#include <cuda_bf16.h>
#include <stdint.h>

namespace din {

constexpr int kL = 200, kD = 64;
#define NCW 3
#define NSLOT 3
constexpr int CHUNK = 128;
constexpr int NTHREADS = NCW * 128 + 128;
#define PREGS 56
#define CREGS 152
constexpr int PROD_REGS = PREGS, CONS_REGS = CREGS;
#define PF_ROWS 8
#define PF_FAST 10
#define PF_SLOW 2000
#define PF_CYCLES 280
#define RED_SLEEP 100
#define K_SEL 1
#define K_LO2 2
#define K_HI1 2
#define K_HI2 2
#define K_NX 2
#define K_BAR 1
#define K_TOP 1
#define NA 4
#define KL 2
#define S0 1
#define D0 5
#define KC 4
#define PF_EARLY 3
#define SLOW_ROUNDS 5
#define SLOW_BY 13
constexpr int NSTATIC = 2;
constexpr int S_TGT = CHUNK * 128;
constexpr int S_HDR = S_TGT + 128;
constexpr int S_FULL = S_HDR + 8;
constexpr int S_EMPTY = S_HDR + 16;
constexpr int S_ROW = S_HDR + 24;
constexpr int S_MASK = S_TGT + 256;
constexpr int S_OUT = S_TGT + 1024;
constexpr int SLOT_BYTES = S_OUT + 4096;
constexpr int RING_BYTES_ = NSLOT * SLOT_BYTES;
constexpr int R_PACE = 2 * RING_BYTES_ + S_TGT + 768;
constexpr int R_START = S_HDR + 32;
constexpr int R_STOP = S_HDR + 44;
constexpr int R_LIST = S_TGT + 512;
constexpr int R_VEC = S_TGT + 768;
constexpr int R_SEL = S_TGT + 896;
constexpr int R_CARRY = SLOT_BYTES + S_TGT + 512;
constexpr int R_TGT0 = (NSLOT - 1) * SLOT_BYTES + S_OUT;
constexpr int RING_BYTES = NSLOT * SLOT_BYTES;
constexpr int SCALES = NCW * RING_BYTES + 32768;
constexpr int SMEM_BYTES = SCALES + 512 + 1024;
__device__ constexpr int w1_at(int i) { return NCW * RING_BYTES + i * 8192; }
static_assert(SMEM_BYTES <= 232448, "shared memory");
constexpr uint32_t H_12 = 0x1f, H_13 = 0x20, H_14 = 0x40, H_15 = 0x80, H_16 = 0x100;
constexpr uint32_t H_GENERAL = 1u << 18, H_FINAL = 1u << 19, H_STOP = 1u << 20, H_NEXT = 0x3fc3fc00;
__device__ __forceinline__ uint32_t size_flag(int rows) { return 1u << ((rows - 57) >> 3); }
constexpr uint32_t ROW_REST = 1u << 30, ROW_MORE = 1u << 31;

__device__ unsigned int g_next;

#define STR2(x) #x
#define STR(x) STR2(x)
template<int V> struct Int { static constexpr int value = V; };
template<int G> __device__ __forceinline__ void g1_bias(float* d, const uint32_t (&bq)[4], uint32_t loSel);
template<int G> __device__ __forceinline__ void g1_step(float* d, const uint32_t* a, uint32_t loH, uint32_t hiH);
template<> __device__ __forceinline__ void g1_bias<4>(float* d, const uint32_t (&bq)[4], uint32_t loSel) {
  asm volatile("{\n.reg .b64 db;\n.reg .b32 zr;\n"
    "mov.b32 zr, 0;\nmov.b64 db, {%20, zr};\n"
    "wgmma.mma_async.sync.aligned.m64n32k16.f32.bf16.bf16 {%0, %1, %2, %3, %4, %5, %6, %7, %8, %9, %10, %11, %12, %13, %14, %15}, {%16, %17, %18, %19}, db, 0, 1, 1, 0;\n}\n"
    : "=f"(d[0]), "=f"(d[1]), "=f"(d[2]), "=f"(d[3]), "=f"(d[4]), "=f"(d[5]), "=f"(d[6]), "=f"(d[7]), "=f"(d[8]), "=f"(d[9]), "=f"(d[10]), "=f"(d[11]), "=f"(d[12]), "=f"(d[13]), "=f"(d[14]), "=f"(d[15])
    : "r"(bq[0]), "r"(bq[1]), "r"(bq[2]), "r"(bq[3]), "r"(loSel)
    : "memory");
}
template<> __device__ __forceinline__ void g1_bias<8>(float* d, const uint32_t (&bq)[4], uint32_t loSel) {
  asm volatile("{\n.reg .b64 db;\n.reg .b32 zr;\n"
    "mov.b32 zr, 0;\nmov.b64 db, {%36, zr};\n"
    "wgmma.mma_async.sync.aligned.m64n64k16.f32.bf16.bf16 {%0, %1, %2, %3, %4, %5, %6, %7, %8, %9, %10, %11, %12, %13, %14, %15, %16, %17, %18, %19, %20, %21, %22, %23, %24, %25, %26, %27, %28, %29, %30, %31}, {%32, %33, %34, %35}, db, 0, 1, 1, 0;\n}\n"
    : "=f"(d[0]), "=f"(d[1]), "=f"(d[2]), "=f"(d[3]), "=f"(d[4]), "=f"(d[5]), "=f"(d[6]), "=f"(d[7]), "=f"(d[8]), "=f"(d[9]), "=f"(d[10]), "=f"(d[11]), "=f"(d[12]), "=f"(d[13]), "=f"(d[14]), "=f"(d[15]), "=f"(d[16]), "=f"(d[17]), "=f"(d[18]), "=f"(d[19]), "=f"(d[20]), "=f"(d[21]), "=f"(d[22]), "=f"(d[23]), "=f"(d[24]), "=f"(d[25]), "=f"(d[26]), "=f"(d[27]), "=f"(d[28]), "=f"(d[29]), "=f"(d[30]), "=f"(d[31])
    : "r"(bq[0]), "r"(bq[1]), "r"(bq[2]), "r"(bq[3]), "r"(loSel)
    : "memory");
}
template<> __device__ __forceinline__ void g1_bias<9>(float* d, const uint32_t (&bq)[4], uint32_t loSel) {
  asm volatile("{\n.reg .b64 db;\n.reg .b32 zr;\n"
    "mov.b32 zr, 0;\nmov.b64 db, {%40, zr};\n"
    "wgmma.mma_async.sync.aligned.m64n72k16.f32.bf16.bf16 {%0, %1, %2, %3, %4, %5, %6, %7, %8, %9, %10, %11, %12, %13, %14, %15, %16, %17, %18, %19, %20, %21, %22, %23, %24, %25, %26, %27, %28, %29, %30, %31, %32, %33, %34, %35}, {%36, %37, %38, %39}, db, 0, 1, 1, 0;\n}\n"
    : "=f"(d[0]), "=f"(d[1]), "=f"(d[2]), "=f"(d[3]), "=f"(d[4]), "=f"(d[5]), "=f"(d[6]), "=f"(d[7]), "=f"(d[8]), "=f"(d[9]), "=f"(d[10]), "=f"(d[11]), "=f"(d[12]), "=f"(d[13]), "=f"(d[14]), "=f"(d[15]), "=f"(d[16]), "=f"(d[17]), "=f"(d[18]), "=f"(d[19]), "=f"(d[20]), "=f"(d[21]), "=f"(d[22]), "=f"(d[23]), "=f"(d[24]), "=f"(d[25]), "=f"(d[26]), "=f"(d[27]), "=f"(d[28]), "=f"(d[29]), "=f"(d[30]), "=f"(d[31]), "=f"(d[32]), "=f"(d[33]), "=f"(d[34]), "=f"(d[35])
    : "r"(bq[0]), "r"(bq[1]), "r"(bq[2]), "r"(bq[3]), "r"(loSel)
    : "memory");
}
template<> __device__ __forceinline__ void g1_bias<10>(float* d, const uint32_t (&bq)[4], uint32_t loSel) {
  asm volatile("{\n.reg .b64 db;\n.reg .b32 zr;\n"
    "mov.b32 zr, 0;\nmov.b64 db, {%44, zr};\n"
    "wgmma.mma_async.sync.aligned.m64n80k16.f32.bf16.bf16 {%0, %1, %2, %3, %4, %5, %6, %7, %8, %9, %10, %11, %12, %13, %14, %15, %16, %17, %18, %19, %20, %21, %22, %23, %24, %25, %26, %27, %28, %29, %30, %31, %32, %33, %34, %35, %36, %37, %38, %39}, {%40, %41, %42, %43}, db, 0, 1, 1, 0;\n}\n"
    : "=f"(d[0]), "=f"(d[1]), "=f"(d[2]), "=f"(d[3]), "=f"(d[4]), "=f"(d[5]), "=f"(d[6]), "=f"(d[7]), "=f"(d[8]), "=f"(d[9]), "=f"(d[10]), "=f"(d[11]), "=f"(d[12]), "=f"(d[13]), "=f"(d[14]), "=f"(d[15]), "=f"(d[16]), "=f"(d[17]), "=f"(d[18]), "=f"(d[19]), "=f"(d[20]), "=f"(d[21]), "=f"(d[22]), "=f"(d[23]), "=f"(d[24]), "=f"(d[25]), "=f"(d[26]), "=f"(d[27]), "=f"(d[28]), "=f"(d[29]), "=f"(d[30]), "=f"(d[31]), "=f"(d[32]), "=f"(d[33]), "=f"(d[34]), "=f"(d[35]), "=f"(d[36]), "=f"(d[37]), "=f"(d[38]), "=f"(d[39])
    : "r"(bq[0]), "r"(bq[1]), "r"(bq[2]), "r"(bq[3]), "r"(loSel)
    : "memory");
}
template<> __device__ __forceinline__ void g1_bias<11>(float* d, const uint32_t (&bq)[4], uint32_t loSel) {
  asm volatile("{\n.reg .b64 db;\n.reg .b32 zr;\n"
    "mov.b32 zr, 0;\nmov.b64 db, {%48, zr};\n"
    "wgmma.mma_async.sync.aligned.m64n88k16.f32.bf16.bf16 {%0, %1, %2, %3, %4, %5, %6, %7, %8, %9, %10, %11, %12, %13, %14, %15, %16, %17, %18, %19, %20, %21, %22, %23, %24, %25, %26, %27, %28, %29, %30, %31, %32, %33, %34, %35, %36, %37, %38, %39, %40, %41, %42, %43}, {%44, %45, %46, %47}, db, 0, 1, 1, 0;\n}\n"
    : "=f"(d[0]), "=f"(d[1]), "=f"(d[2]), "=f"(d[3]), "=f"(d[4]), "=f"(d[5]), "=f"(d[6]), "=f"(d[7]), "=f"(d[8]), "=f"(d[9]), "=f"(d[10]), "=f"(d[11]), "=f"(d[12]), "=f"(d[13]), "=f"(d[14]), "=f"(d[15]), "=f"(d[16]), "=f"(d[17]), "=f"(d[18]), "=f"(d[19]), "=f"(d[20]), "=f"(d[21]), "=f"(d[22]), "=f"(d[23]), "=f"(d[24]), "=f"(d[25]), "=f"(d[26]), "=f"(d[27]), "=f"(d[28]), "=f"(d[29]), "=f"(d[30]), "=f"(d[31]), "=f"(d[32]), "=f"(d[33]), "=f"(d[34]), "=f"(d[35]), "=f"(d[36]), "=f"(d[37]), "=f"(d[38]), "=f"(d[39]), "=f"(d[40]), "=f"(d[41]), "=f"(d[42]), "=f"(d[43])
    : "r"(bq[0]), "r"(bq[1]), "r"(bq[2]), "r"(bq[3]), "r"(loSel)
    : "memory");
}
template<> __device__ __forceinline__ void g1_bias<12>(float* d, const uint32_t (&bq)[4], uint32_t loSel) {
  asm volatile("{\n.reg .b64 db;\n.reg .b32 zr;\n"
    "mov.b32 zr, 0;\nmov.b64 db, {%52, zr};\n"
    "wgmma.mma_async.sync.aligned.m64n96k16.f32.bf16.bf16 {%0, %1, %2, %3, %4, %5, %6, %7, %8, %9, %10, %11, %12, %13, %14, %15, %16, %17, %18, %19, %20, %21, %22, %23, %24, %25, %26, %27, %28, %29, %30, %31, %32, %33, %34, %35, %36, %37, %38, %39, %40, %41, %42, %43, %44, %45, %46, %47}, {%48, %49, %50, %51}, db, 0, 1, 1, 0;\n}\n"
    : "=f"(d[0]), "=f"(d[1]), "=f"(d[2]), "=f"(d[3]), "=f"(d[4]), "=f"(d[5]), "=f"(d[6]), "=f"(d[7]), "=f"(d[8]), "=f"(d[9]), "=f"(d[10]), "=f"(d[11]), "=f"(d[12]), "=f"(d[13]), "=f"(d[14]), "=f"(d[15]), "=f"(d[16]), "=f"(d[17]), "=f"(d[18]), "=f"(d[19]), "=f"(d[20]), "=f"(d[21]), "=f"(d[22]), "=f"(d[23]), "=f"(d[24]), "=f"(d[25]), "=f"(d[26]), "=f"(d[27]), "=f"(d[28]), "=f"(d[29]), "=f"(d[30]), "=f"(d[31]), "=f"(d[32]), "=f"(d[33]), "=f"(d[34]), "=f"(d[35]), "=f"(d[36]), "=f"(d[37]), "=f"(d[38]), "=f"(d[39]), "=f"(d[40]), "=f"(d[41]), "=f"(d[42]), "=f"(d[43]), "=f"(d[44]), "=f"(d[45]), "=f"(d[46]), "=f"(d[47])
    : "r"(bq[0]), "r"(bq[1]), "r"(bq[2]), "r"(bq[3]), "r"(loSel)
    : "memory");
}
template<> __device__ __forceinline__ void g1_step<4>(float* d, const uint32_t* a, uint32_t loH, uint32_t hiH) {
  asm volatile("{\n.reg .b64 db;\nmov.b64 db, {%20, %21};\n"
    "wgmma.mma_async.sync.aligned.m64n32k16.f32.bf16.bf16 {%0, %1, %2, %3, %4, %5, %6, %7, %8, %9, %10, %11, %12, %13, %14, %15}, {%16, %17, %18, %19}, db, 1, 1, 1, 0;\n}\n"
    : "+f"(d[0]), "+f"(d[1]), "+f"(d[2]), "+f"(d[3]), "+f"(d[4]), "+f"(d[5]), "+f"(d[6]), "+f"(d[7]), "+f"(d[8]), "+f"(d[9]), "+f"(d[10]), "+f"(d[11]), "+f"(d[12]), "+f"(d[13]), "+f"(d[14]), "+f"(d[15])
    : "r"(a[0]), "r"(a[1]), "r"(a[2]), "r"(a[3]), "r"(loH), "r"(hiH)
    : "memory");
}
template<> __device__ __forceinline__ void g1_step<8>(float* d, const uint32_t* a, uint32_t loH, uint32_t hiH) {
  asm volatile("{\n.reg .b64 db;\nmov.b64 db, {%36, %37};\n"
    "wgmma.mma_async.sync.aligned.m64n64k16.f32.bf16.bf16 {%0, %1, %2, %3, %4, %5, %6, %7, %8, %9, %10, %11, %12, %13, %14, %15, %16, %17, %18, %19, %20, %21, %22, %23, %24, %25, %26, %27, %28, %29, %30, %31}, {%32, %33, %34, %35}, db, 1, 1, 1, 0;\n}\n"
    : "+f"(d[0]), "+f"(d[1]), "+f"(d[2]), "+f"(d[3]), "+f"(d[4]), "+f"(d[5]), "+f"(d[6]), "+f"(d[7]), "+f"(d[8]), "+f"(d[9]), "+f"(d[10]), "+f"(d[11]), "+f"(d[12]), "+f"(d[13]), "+f"(d[14]), "+f"(d[15]), "+f"(d[16]), "+f"(d[17]), "+f"(d[18]), "+f"(d[19]), "+f"(d[20]), "+f"(d[21]), "+f"(d[22]), "+f"(d[23]), "+f"(d[24]), "+f"(d[25]), "+f"(d[26]), "+f"(d[27]), "+f"(d[28]), "+f"(d[29]), "+f"(d[30]), "+f"(d[31])
    : "r"(a[0]), "r"(a[1]), "r"(a[2]), "r"(a[3]), "r"(loH), "r"(hiH)
    : "memory");
}
template<> __device__ __forceinline__ void g1_step<9>(float* d, const uint32_t* a, uint32_t loH, uint32_t hiH) {
  asm volatile("{\n.reg .b64 db;\nmov.b64 db, {%40, %41};\n"
    "wgmma.mma_async.sync.aligned.m64n72k16.f32.bf16.bf16 {%0, %1, %2, %3, %4, %5, %6, %7, %8, %9, %10, %11, %12, %13, %14, %15, %16, %17, %18, %19, %20, %21, %22, %23, %24, %25, %26, %27, %28, %29, %30, %31, %32, %33, %34, %35}, {%36, %37, %38, %39}, db, 1, 1, 1, 0;\n}\n"
    : "+f"(d[0]), "+f"(d[1]), "+f"(d[2]), "+f"(d[3]), "+f"(d[4]), "+f"(d[5]), "+f"(d[6]), "+f"(d[7]), "+f"(d[8]), "+f"(d[9]), "+f"(d[10]), "+f"(d[11]), "+f"(d[12]), "+f"(d[13]), "+f"(d[14]), "+f"(d[15]), "+f"(d[16]), "+f"(d[17]), "+f"(d[18]), "+f"(d[19]), "+f"(d[20]), "+f"(d[21]), "+f"(d[22]), "+f"(d[23]), "+f"(d[24]), "+f"(d[25]), "+f"(d[26]), "+f"(d[27]), "+f"(d[28]), "+f"(d[29]), "+f"(d[30]), "+f"(d[31]), "+f"(d[32]), "+f"(d[33]), "+f"(d[34]), "+f"(d[35])
    : "r"(a[0]), "r"(a[1]), "r"(a[2]), "r"(a[3]), "r"(loH), "r"(hiH)
    : "memory");
}
template<> __device__ __forceinline__ void g1_step<10>(float* d, const uint32_t* a, uint32_t loH, uint32_t hiH) {
  asm volatile("{\n.reg .b64 db;\nmov.b64 db, {%44, %45};\n"
    "wgmma.mma_async.sync.aligned.m64n80k16.f32.bf16.bf16 {%0, %1, %2, %3, %4, %5, %6, %7, %8, %9, %10, %11, %12, %13, %14, %15, %16, %17, %18, %19, %20, %21, %22, %23, %24, %25, %26, %27, %28, %29, %30, %31, %32, %33, %34, %35, %36, %37, %38, %39}, {%40, %41, %42, %43}, db, 1, 1, 1, 0;\n}\n"
    : "+f"(d[0]), "+f"(d[1]), "+f"(d[2]), "+f"(d[3]), "+f"(d[4]), "+f"(d[5]), "+f"(d[6]), "+f"(d[7]), "+f"(d[8]), "+f"(d[9]), "+f"(d[10]), "+f"(d[11]), "+f"(d[12]), "+f"(d[13]), "+f"(d[14]), "+f"(d[15]), "+f"(d[16]), "+f"(d[17]), "+f"(d[18]), "+f"(d[19]), "+f"(d[20]), "+f"(d[21]), "+f"(d[22]), "+f"(d[23]), "+f"(d[24]), "+f"(d[25]), "+f"(d[26]), "+f"(d[27]), "+f"(d[28]), "+f"(d[29]), "+f"(d[30]), "+f"(d[31]), "+f"(d[32]), "+f"(d[33]), "+f"(d[34]), "+f"(d[35]), "+f"(d[36]), "+f"(d[37]), "+f"(d[38]), "+f"(d[39])
    : "r"(a[0]), "r"(a[1]), "r"(a[2]), "r"(a[3]), "r"(loH), "r"(hiH)
    : "memory");
}
template<> __device__ __forceinline__ void g1_step<11>(float* d, const uint32_t* a, uint32_t loH, uint32_t hiH) {
  asm volatile("{\n.reg .b64 db;\nmov.b64 db, {%48, %49};\n"
    "wgmma.mma_async.sync.aligned.m64n88k16.f32.bf16.bf16 {%0, %1, %2, %3, %4, %5, %6, %7, %8, %9, %10, %11, %12, %13, %14, %15, %16, %17, %18, %19, %20, %21, %22, %23, %24, %25, %26, %27, %28, %29, %30, %31, %32, %33, %34, %35, %36, %37, %38, %39, %40, %41, %42, %43}, {%44, %45, %46, %47}, db, 1, 1, 1, 0;\n}\n"
    : "+f"(d[0]), "+f"(d[1]), "+f"(d[2]), "+f"(d[3]), "+f"(d[4]), "+f"(d[5]), "+f"(d[6]), "+f"(d[7]), "+f"(d[8]), "+f"(d[9]), "+f"(d[10]), "+f"(d[11]), "+f"(d[12]), "+f"(d[13]), "+f"(d[14]), "+f"(d[15]), "+f"(d[16]), "+f"(d[17]), "+f"(d[18]), "+f"(d[19]), "+f"(d[20]), "+f"(d[21]), "+f"(d[22]), "+f"(d[23]), "+f"(d[24]), "+f"(d[25]), "+f"(d[26]), "+f"(d[27]), "+f"(d[28]), "+f"(d[29]), "+f"(d[30]), "+f"(d[31]), "+f"(d[32]), "+f"(d[33]), "+f"(d[34]), "+f"(d[35]), "+f"(d[36]), "+f"(d[37]), "+f"(d[38]), "+f"(d[39]), "+f"(d[40]), "+f"(d[41]), "+f"(d[42]), "+f"(d[43])
    : "r"(a[0]), "r"(a[1]), "r"(a[2]), "r"(a[3]), "r"(loH), "r"(hiH)
    : "memory");
}
template<> __device__ __forceinline__ void g1_step<12>(float* d, const uint32_t* a, uint32_t loH, uint32_t hiH) {
  asm volatile("{\n.reg .b64 db;\nmov.b64 db, {%52, %53};\n"
    "wgmma.mma_async.sync.aligned.m64n96k16.f32.bf16.bf16 {%0, %1, %2, %3, %4, %5, %6, %7, %8, %9, %10, %11, %12, %13, %14, %15, %16, %17, %18, %19, %20, %21, %22, %23, %24, %25, %26, %27, %28, %29, %30, %31, %32, %33, %34, %35, %36, %37, %38, %39, %40, %41, %42, %43, %44, %45, %46, %47}, {%48, %49, %50, %51}, db, 1, 1, 1, 0;\n}\n"
    : "+f"(d[0]), "+f"(d[1]), "+f"(d[2]), "+f"(d[3]), "+f"(d[4]), "+f"(d[5]), "+f"(d[6]), "+f"(d[7]), "+f"(d[8]), "+f"(d[9]), "+f"(d[10]), "+f"(d[11]), "+f"(d[12]), "+f"(d[13]), "+f"(d[14]), "+f"(d[15]), "+f"(d[16]), "+f"(d[17]), "+f"(d[18]), "+f"(d[19]), "+f"(d[20]), "+f"(d[21]), "+f"(d[22]), "+f"(d[23]), "+f"(d[24]), "+f"(d[25]), "+f"(d[26]), "+f"(d[27]), "+f"(d[28]), "+f"(d[29]), "+f"(d[30]), "+f"(d[31]), "+f"(d[32]), "+f"(d[33]), "+f"(d[34]), "+f"(d[35]), "+f"(d[36]), "+f"(d[37]), "+f"(d[38]), "+f"(d[39]), "+f"(d[40]), "+f"(d[41]), "+f"(d[42]), "+f"(d[43]), "+f"(d[44]), "+f"(d[45]), "+f"(d[46]), "+f"(d[47])
    : "r"(a[0]), "r"(a[1]), "r"(a[2]), "r"(a[3]), "r"(loH), "r"(hiH)
    : "memory");
}
__device__ __forceinline__ void g2_first(float (&o)[16], const uint32_t* a, uint32_t loH, uint32_t meta, uint32_t hiH) {
  asm volatile("{\n.reg .b64 db;\nmov.b64 db, {%20, %22};\n"
    "wgmma.mma_async.sp.sync.aligned.m64n32k32.f32.bf16.bf16 {%0, %1, %2, %3, %4, %5, %6, %7, %8, %9, %10, %11, %12, %13, %14, %15}, {%16, %17, %18, %19}, db, %21, 0, 0, 1, 1, 1;\n}\n"
    : "=f"(o[0]), "=f"(o[1]), "=f"(o[2]), "=f"(o[3]), "=f"(o[4]), "=f"(o[5]), "=f"(o[6]), "=f"(o[7]), "=f"(o[8]), "=f"(o[9]), "=f"(o[10]), "=f"(o[11]), "=f"(o[12]), "=f"(o[13]), "=f"(o[14]), "=f"(o[15])
    : "r"(a[0]), "r"(a[1]), "r"(a[2]), "r"(a[3]), "r"(loH), "r"(meta), "r"(hiH)
    : "memory");
}
__device__ __forceinline__ void g2_more(float (&o)[16], const uint32_t* a, uint32_t loH, uint32_t meta, uint32_t hiH) {
  asm volatile("{\n.reg .b64 db;\nmov.b64 db, {%20, %22};\n"
    "wgmma.mma_async.sp.sync.aligned.m64n32k32.f32.bf16.bf16 {%0, %1, %2, %3, %4, %5, %6, %7, %8, %9, %10, %11, %12, %13, %14, %15}, {%16, %17, %18, %19}, db, %21, 0, 1, 1, 1, 1;\n}\n"
    : "+f"(o[0]), "+f"(o[1]), "+f"(o[2]), "+f"(o[3]), "+f"(o[4]), "+f"(o[5]), "+f"(o[6]), "+f"(o[7]), "+f"(o[8]), "+f"(o[9]), "+f"(o[10]), "+f"(o[11]), "+f"(o[12]), "+f"(o[13]), "+f"(o[14]), "+f"(o[15])
    : "r"(a[0]), "r"(a[1]), "r"(a[2]), "r"(a[3]), "r"(loH), "r"(meta), "r"(hiH)
    : "memory");
}
template<int N> __device__ __forceinline__ void mma_wait(float* d, Int<4>) {
  asm volatile("wgmma.wait_group.sync.aligned %16;"
    : "+f"(d[0]), "+f"(d[1]), "+f"(d[2]), "+f"(d[3]), "+f"(d[4]), "+f"(d[5]), "+f"(d[6]), "+f"(d[7]), "+f"(d[8]), "+f"(d[9]), "+f"(d[10]), "+f"(d[11]), "+f"(d[12]), "+f"(d[13]), "+f"(d[14]), "+f"(d[15])
    : "n"(N) : "memory");
}
template<int N> __device__ __forceinline__ void mma_wait(float* d, Int<8>) {
  asm volatile("wgmma.wait_group.sync.aligned %32;"
    : "+f"(d[0]), "+f"(d[1]), "+f"(d[2]), "+f"(d[3]), "+f"(d[4]), "+f"(d[5]), "+f"(d[6]), "+f"(d[7]), "+f"(d[8]), "+f"(d[9]), "+f"(d[10]), "+f"(d[11]), "+f"(d[12]), "+f"(d[13]), "+f"(d[14]), "+f"(d[15]), "+f"(d[16]), "+f"(d[17]), "+f"(d[18]), "+f"(d[19]), "+f"(d[20]), "+f"(d[21]), "+f"(d[22]), "+f"(d[23]), "+f"(d[24]), "+f"(d[25]), "+f"(d[26]), "+f"(d[27]), "+f"(d[28]), "+f"(d[29]), "+f"(d[30]), "+f"(d[31])
    : "n"(N) : "memory");
}
template<int N> __device__ __forceinline__ void mma_wait(float* d, Int<9>) {
  asm volatile("wgmma.wait_group.sync.aligned %36;"
    : "+f"(d[0]), "+f"(d[1]), "+f"(d[2]), "+f"(d[3]), "+f"(d[4]), "+f"(d[5]), "+f"(d[6]), "+f"(d[7]), "+f"(d[8]), "+f"(d[9]), "+f"(d[10]), "+f"(d[11]), "+f"(d[12]), "+f"(d[13]), "+f"(d[14]), "+f"(d[15]), "+f"(d[16]), "+f"(d[17]), "+f"(d[18]), "+f"(d[19]), "+f"(d[20]), "+f"(d[21]), "+f"(d[22]), "+f"(d[23]), "+f"(d[24]), "+f"(d[25]), "+f"(d[26]), "+f"(d[27]), "+f"(d[28]), "+f"(d[29]), "+f"(d[30]), "+f"(d[31]), "+f"(d[32]), "+f"(d[33]), "+f"(d[34]), "+f"(d[35])
    : "n"(N) : "memory");
}
template<int N> __device__ __forceinline__ void mma_wait(float* d, Int<10>) {
  asm volatile("wgmma.wait_group.sync.aligned %40;"
    : "+f"(d[0]), "+f"(d[1]), "+f"(d[2]), "+f"(d[3]), "+f"(d[4]), "+f"(d[5]), "+f"(d[6]), "+f"(d[7]), "+f"(d[8]), "+f"(d[9]), "+f"(d[10]), "+f"(d[11]), "+f"(d[12]), "+f"(d[13]), "+f"(d[14]), "+f"(d[15]), "+f"(d[16]), "+f"(d[17]), "+f"(d[18]), "+f"(d[19]), "+f"(d[20]), "+f"(d[21]), "+f"(d[22]), "+f"(d[23]), "+f"(d[24]), "+f"(d[25]), "+f"(d[26]), "+f"(d[27]), "+f"(d[28]), "+f"(d[29]), "+f"(d[30]), "+f"(d[31]), "+f"(d[32]), "+f"(d[33]), "+f"(d[34]), "+f"(d[35]), "+f"(d[36]), "+f"(d[37]), "+f"(d[38]), "+f"(d[39])
    : "n"(N) : "memory");
}
template<int N> __device__ __forceinline__ void mma_wait(float* d, Int<11>) {
  asm volatile("wgmma.wait_group.sync.aligned %44;"
    : "+f"(d[0]), "+f"(d[1]), "+f"(d[2]), "+f"(d[3]), "+f"(d[4]), "+f"(d[5]), "+f"(d[6]), "+f"(d[7]), "+f"(d[8]), "+f"(d[9]), "+f"(d[10]), "+f"(d[11]), "+f"(d[12]), "+f"(d[13]), "+f"(d[14]), "+f"(d[15]), "+f"(d[16]), "+f"(d[17]), "+f"(d[18]), "+f"(d[19]), "+f"(d[20]), "+f"(d[21]), "+f"(d[22]), "+f"(d[23]), "+f"(d[24]), "+f"(d[25]), "+f"(d[26]), "+f"(d[27]), "+f"(d[28]), "+f"(d[29]), "+f"(d[30]), "+f"(d[31]), "+f"(d[32]), "+f"(d[33]), "+f"(d[34]), "+f"(d[35]), "+f"(d[36]), "+f"(d[37]), "+f"(d[38]), "+f"(d[39]), "+f"(d[40]), "+f"(d[41]), "+f"(d[42]), "+f"(d[43])
    : "n"(N) : "memory");
}
template<int N> __device__ __forceinline__ void mma_wait(float* d, Int<12>) {
  asm volatile("wgmma.wait_group.sync.aligned %48;"
    : "+f"(d[0]), "+f"(d[1]), "+f"(d[2]), "+f"(d[3]), "+f"(d[4]), "+f"(d[5]), "+f"(d[6]), "+f"(d[7]), "+f"(d[8]), "+f"(d[9]), "+f"(d[10]), "+f"(d[11]), "+f"(d[12]), "+f"(d[13]), "+f"(d[14]), "+f"(d[15]), "+f"(d[16]), "+f"(d[17]), "+f"(d[18]), "+f"(d[19]), "+f"(d[20]), "+f"(d[21]), "+f"(d[22]), "+f"(d[23]), "+f"(d[24]), "+f"(d[25]), "+f"(d[26]), "+f"(d[27]), "+f"(d[28]), "+f"(d[29]), "+f"(d[30]), "+f"(d[31]), "+f"(d[32]), "+f"(d[33]), "+f"(d[34]), "+f"(d[35]), "+f"(d[36]), "+f"(d[37]), "+f"(d[38]), "+f"(d[39]), "+f"(d[40]), "+f"(d[41]), "+f"(d[42]), "+f"(d[43]), "+f"(d[44]), "+f"(d[45]), "+f"(d[46]), "+f"(d[47])
    : "n"(N) : "memory");
}

__device__ __forceinline__ uint32_t smem_u32(const void* p) { return (uint32_t)__cvta_generic_to_shared(p); }

__device__ __forceinline__ void mbar_init(uint32_t bar, uint32_t cnt) {
  asm volatile("mbarrier.init.shared::cta.b64 [%0], %1;" :: "r"(bar), "r"(cnt) : "memory");
}
__device__ __forceinline__ void mbar_arrive(uint32_t bar) {
  asm volatile("mbarrier.arrive.shared::cta.b64 _, [%0];" :: "r"(bar) : "memory");
}
__device__ __forceinline__ void mbar_wait(uint32_t bar, uint32_t parity) {
  asm volatile("{\n.reg .pred p;\n.reg .u32 n;\n"
               "mov.u32 n, 0;\n"
               "WAIT_LOOP:\n"
               "mbarrier.try_wait.parity.shared::cta.b64 p, [%0], %1;\n"
               "@p bra.uni WAIT_DONE;\n"
               "add.u32 n, n, 1;\n"
               "setp.lt.u32 p, n, 0x1000000;\n"
               "@p bra.uni WAIT_LOOP;\n"
               "trap;\n"
               "WAIT_DONE:\n}\n"
               :: "r"(bar), "r"(parity) : "memory");
}
__device__ __forceinline__ uint32_t mbar_test(uint32_t bar, uint32_t parity) {
  uint32_t ok;
  asm volatile("{\n.reg .pred p;\nmbarrier.test_wait.parity.shared::cta.b64 p, [%1], %2;\nselp.u32 %0, 1, 0, p;\n}\n"
               : "=r"(ok) : "r"(bar), "r"(parity) : "memory");
  return ok;
}
__device__ __forceinline__ void cp_async16(uint32_t dst, const void* src) {
  asm volatile("cp.async.cg.shared.global [%0], [%1], 16;" :: "r"(dst), "l"(src) : "memory");
}
template<int T, int I, bool Z>
__device__ __forceinline__ void cp_row(uint32_t dst, uint64_t& a, uint32_t rows4, uint32_t base, int left, uint64_t pol) {
#define DIN_ADDR "mov.b64 {x, y}, %0;\ndp4a.u32.u32 x, %2, %8, %5;\nmov.b64 %0, {x, y};\n"
  if (Z)
    asm volatile("{\n.reg .u32 x, y;\n.reg .pred p;\n" DIN_ADDR "setp.le.s32 p, %6, %7;\n"
                 "cp.async.cg.shared.global.L2::cache_hint [%1 + %4], [%0], 16, p, %3;\n}\n"
                 : "+l"(a) : "r"(dst), "r"(rows4), "l"(pol), "n"(T * 2048), "r"(base), "r"(left), "n"(T * 16 + I), "n"(0x80u << 8 * I) : "memory");
  else
    asm volatile("{\n.reg .u32 x, y;\n" DIN_ADDR
                 "cp.async.cg.shared.global.L2::cache_hint [%1 + %4], [%0], 16, %3;\n}\n"
                 : "+l"(a) : "r"(dst), "r"(rows4), "l"(pol), "n"(T * 2048), "r"(base), "r"(left), "n"(T * 16 + I), "n"(0x80u << 8 * I) : "memory");
}
template<int T, bool Z>
__device__ __forceinline__ void cp_group(const uint32_t (&dst)[4], uint64_t& a, uint32_t rows4, uint32_t base, int left, uint64_t pol) {
  cp_row<T, 0, Z>(dst[0], a, rows4, base, left, pol);
  cp_row<T, 1, Z>(dst[1], a, rows4, base, left, pol);
  cp_row<T, 2, Z>(dst[2], a, rows4, base, left, pol);
  cp_row<T, 3, Z>(dst[3], a, rows4, base, left, pol);
}
__device__ __forceinline__ uint32_t prmt(uint32_t a, uint32_t b, uint32_t sel) {
  uint32_t d;
  asm("prmt.b32 %0, %1, %2, %3;" : "=r"(d) : "r"(a), "r"(b), "r"(sel));
  return d;
}
__device__ __forceinline__ uint32_t ballot_bit(uint32_t x, uint32_t bit) {
  uint32_t d;
  asm volatile("{\n.reg .pred p;\n.reg .u32 t;\nand.b32 t, %1, %2;\nsetp.ne.u32 p, t, 0;\nvote.sync.ballot.b32 %0, p, 0xffffffff;\n}\n"
               : "=r"(d) : "r"(x), "r"(bit));
  return d;
}
__device__ __forceinline__ uint4 load_mask(const void* mask, uint32_t b, uint32_t i) {
  uint4 m;
  asm volatile("ld.global.nc.L1::no_allocate.v4.u32 {%0,%1,%2,%3}, [%4];"
               : "=r"(m.x), "=r"(m.y), "=r"(m.z), "=r"(m.w) : "l"(reinterpret_cast<const uint4*>(mask) + (b * 25u + i)));
  return m;
}
__device__ __forceinline__ uint32_t nonzero_as_one(uint32_t x) {
  uint32_t d;
  asm("set.neu.bf16x2.bf16x2 %0, %1, %2;" : "=r"(d) : "r"(x), "r"(0u));
  return d;
}
__device__ __forceinline__ void cp_async_arrive_noinc(uint32_t bar) {
  asm volatile("cp.async.mbarrier.arrive.noinc.shared::cta.b64 [%0];" :: "r"(bar) : "memory");
}
__device__ __forceinline__ void ldsm_x4(uint32_t addr, uint32_t& r0, uint32_t& r1, uint32_t& r2, uint32_t& r3) {
  asm volatile("ldmatrix.sync.aligned.m8n8.x4.shared.b16 {%0,%1,%2,%3}, [%4];"
               : "=r"(r0), "=r"(r1), "=r"(r2), "=r"(r3) : "r"(addr) : "memory");
}
__device__ __forceinline__ void ldsm_x4_t(uint32_t addr, uint32_t& r0, uint32_t& r1, uint32_t& r2, uint32_t& r3) {
  asm volatile("ldmatrix.sync.aligned.m8n8.x4.trans.shared.b16 {%0,%1,%2,%3}, [%4];"
               : "=r"(r0), "=r"(r1), "=r"(r2), "=r"(r3) : "r"(addr) : "memory");
}
__device__ __forceinline__ void stsm_x4_t(uint32_t addr, uint32_t r0, uint32_t r1, uint32_t r2, uint32_t r3) {
  asm volatile("stmatrix.sync.aligned.m8n8.x4.trans.shared.b16 [%0], {%1,%2,%3,%4};"
               :: "r"(addr), "r"(r0), "r"(r1), "r"(r2), "r"(r3) : "memory");
}
__device__ __forceinline__ uint32_t hfma2_bf16(uint32_t a, uint32_t b, uint32_t c) {
  uint32_t d;
  asm volatile("fma.rn.bf16x2 %0, %1, %2, %3;" : "=r"(d) : "r"(a), "r"(b), "r"(c));
  return d;
}
__device__ __forceinline__ uint32_t pack_bf16(float lo, float hi) {
  uint32_t d;
  asm("cvt.rn.bf16x2.f32 %0, %1, %2;" : "=r"(d) : "f"(hi), "f"(lo));
  return d;
}
__device__ __forceinline__ uint32_t lds32(uint32_t a) {
  uint32_t v; asm volatile("ld.shared.u32 %0, [%1];" : "=r"(v) : "r"(a) : "memory"); return v;
}
__device__ __forceinline__ uint32_t lds16(uint32_t a) {
  uint32_t v; asm volatile("ld.shared.u16 %0, [%1];" : "=r"(v) : "r"(a) : "memory"); return v;
}
__device__ __forceinline__ void sts32(uint32_t a, uint32_t v) {
  asm volatile("st.shared.u32 [%0], %1;" :: "r"(a), "r"(v) : "memory");
}
__device__ __forceinline__ void sts16(uint32_t a, uint32_t v) {
  asm volatile("st.shared.u16 [%0], %1;" :: "r"(a), "h"((unsigned short)v) : "memory");
}
__device__ __forceinline__ void sts8(uint32_t a, uint32_t v) {
  asm volatile("st.shared.u8 [%0], %1;" :: "r"(a), "r"(v) : "memory");
}
constexpr uint32_t DESC_ROWS = 0x40000040u, DESC_HALVES = 0x80000020u;
__device__ __forceinline__ uint32_t desc_lo(uint32_t addr) { return ((addr & 0x3FFFF) >> 4) | (1u << 16); }

__device__ __forceinline__ uint4 lds128(uint32_t a) {
  uint4 v;
  asm volatile("ld.shared.v4.u32 {%0,%1,%2,%3}, [%4];" : "=r"(v.x), "=r"(v.y), "=r"(v.z), "=r"(v.w) : "r"(a) : "memory");
  return v;
}
__device__ __forceinline__ void sts128(uint32_t a, uint4 v) {
  asm volatile("st.shared.v4.u32 [%0], {%1,%2,%3,%4};" :: "r"(a), "r"(v.x), "r"(v.y), "r"(v.z), "r"(v.w) : "memory");
}
__device__ __forceinline__ void prefetch_l2(const void* p, uint32_t bytes) {
  asm volatile("cp.async.bulk.prefetch.L2.global [%0], %1;" :: "l"(p), "r"(bytes) : "memory");
}

__device__ __forceinline__ void cut_here(uint32_t& any, uint32_t zero) {
  asm volatile("{\n.reg .pred p;\nsetp.ne.u32 p, %1, 0;\n@p mov.u32 %0, %%clock;\n}\n" : "+r"(any) : "r"(zero) : "memory");
}
__device__ __forceinline__ void mma_fence() { asm volatile("wgmma.fence.sync.aligned;" ::: "memory"); }
__device__ __forceinline__ void mma_commit() { asm volatile("wgmma.commit_group.sync.aligned;" ::: "memory"); }
template<bool FIRST>
__device__ __forceinline__ void hmma(float (&c)[4], const uint32_t* a, uint32_t b0, uint32_t b1) {
  if (FIRST)
    asm volatile("mma.sync.aligned.m16n8k16.row.col.f32.bf16.bf16.f32 {%0,%1,%2,%3}, {%4,%5,%6,%7}, {%8,%9}, {%10,%10,%10,%10};"
                 : "=f"(c[0]), "=f"(c[1]), "=f"(c[2]), "=f"(c[3]) : "r"(a[0]), "r"(a[1]), "r"(a[2]), "r"(a[3]), "r"(b0), "r"(b1), "f"(0.f));
  else
    asm volatile("mma.sync.aligned.m16n8k16.row.col.f32.bf16.bf16.f32 {%0,%1,%2,%3}, {%4,%5,%6,%7}, {%8,%9}, {%0,%1,%2,%3};"
                 : "+f"(c[0]), "+f"(c[1]), "+f"(c[2]), "+f"(c[3]) : "r"(a[0]), "r"(a[1]), "r"(a[2]), "r"(a[3]), "r"(b0), "r"(b1));
}
__device__ __forceinline__ void tanh_some(float* d, int i0, int i1) {
#pragma unroll
  for (int i = i0; i < i1; i++) asm volatile("tanh.approx.f32 %0, %0;" : "+f"(d[i ^ 2]));
}
__device__ __forceinline__ uint32_t mix(const float* d, int i, float r) {
  uint32_t p;
  asm volatile("{\n.reg .f32 x, y;\nfma.rn.f32 x, %3, %5, %1;\nfma.rn.f32 y, %4, %5, %2;\ncvt.rn.bf16x2.f32 %0, y, x;\n}\n"
               : "=r"(p) : "f"(d[4 * i]), "f"(d[4 * i + 1]), "f"(d[4 * i + 2]), "f"(d[4 * i + 3]), "f"(r));
  return p;
}
__device__ __forceinline__ uint32_t sums_at(uint32_t d) { return S_OUT + (d ^ ((d >> 3) & 1)) * 16; }
template<int K> __device__ __forceinline__ uint32_t keep(uint32_t x) { return K ? __shfl_sync(0xffffffffu, x, 0) : x; }

template<int PF_M, int PF_T>
__global__ void __launch_bounds__(NTHREADS, 1)
din_kernel(const __nv_bfloat16* __restrict__ mask, const __nv_bfloat16* __restrict__ target, int B, int grid,
           const __nv_bfloat16* __restrict__ w1, const __nv_bfloat16* __restrict__ hist,
           const __nv_bfloat16* __restrict__ b1, const __nv_bfloat16* __restrict__ w2,
           const __nv_bfloat16* __restrict__ b2, __nv_bfloat16* __restrict__ out, unsigned int* counter, int pace16,
           int slow_pace, int slow_from) {
  const uint32_t tid = threadIdx.x, pf_at = blockIdx.x * NTHREADS + tid;
  asm volatile("{\n.reg .pred p;\nprefetch.global.L2 [%0];\nsetp.gt.u32 p, %1, 0x7ffffff0;\n@p exit;\n}\n"
               :: "l"(reinterpret_cast<const char*>(mask) + (size_t)pf_at * PF_M), "r"(blockIdx.x) : "memory");
  asm volatile("prefetch.global.L2 [%0];" :: "l"(reinterpret_cast<const char*>(target) + (size_t)pf_at * PF_T));
  extern __shared__ unsigned char smem_raw[];
  const uint32_t sb = (smem_u32(smem_raw) + 1023u) & ~1023u;
  const int lane = tid & 31;
  const uint32_t gwarp = __shfl_sync(0xffffffffu, pf_at >> 5, 0), cta = gwarp / (NTHREADS / 32);
  const int warp = gwarp % (NTHREADS / 32);
#define ACT NCW
  const int bstep = ACT * grid;

  if (warp < NCW * 4) {
    const int wg = warp >> 2, w = warp & 3;
    const int g = lane >> 2;
    const uint32_t ring = sb + wg * RING_BYTES;
    const bool active = wg * grid + (int)cta < B && wg < ACT;
    {
      const int t = tid & 127;
      const uint32_t dst = sb + ((t ^ ((t >> 3) & 7)) << 4);
      const char* src = reinterpret_cast<const char*>(w1) + t * 16;
#pragma unroll
      for (int i = 0; i < 4; i++) cp_async16(dst + w1_at(i) + wg * 2048, src + i * 8192 + wg * 2048);
      cp_async16(dst + w1_at(0) + wg * 8192 + 6144, src + wg * 8192 + 6144);
      if (wg == 0) cp_async16(dst + w1_at(3) + 6144, src + 3 * 8192 + 6144);
      if (lane < 8) {
        if (w == 0 && active) cp_async16(ring + R_TGT0 + lane * 16, target + (size_t)(wg * grid + cta) * kD + lane * 8);
        if (w == 1 && wg < 2) cp_async16(ring + R_VEC + lane * 16, (wg ? w2 : b1) + lane * 8);
      }
    }
    if (w == 2) sts32(ring + R_SEL + lane * 4, 0x3e803e80u);
    uint32_t rb2;
    asm volatile("ld.global.nc.u16 %0, [%1];" : "=r"(rb2) : "l"(b2));
    asm volatile("setmaxnreg.inc.sync.aligned.u32 %0;" :: "n"(CONS_REGS));
    asm volatile("cp.async.wait_all;" ::: "memory");
    asm volatile("bar.sync 1, %0;" :: "n"(NCW * 160) : "memory");
    float r;
    uint32_t cq, swap, half2, bf[4];
    {
      const uint32_t v2 = sb + RING_BYTES + R_VEC + ((lane & 24) * 2 + (lane & 7)) * 2;
      const float x = __uint_as_float(lds16(v2) << 16), y = __uint_as_float(lds16(v2 + 16) << 16);
      float c = x + y;
#pragma unroll
      for (int o = 16; o; o >>= 1) c += __shfl_xor_sync(0xffffffffu, c, o);
      c = 0.5f * c + __uint_as_float(rb2 << 16);
      const bool sw = fabsf(y) > fabsf(x);
      const float u = sw ? y : x, v = sw ? x : y;
      const bool off = !(fabsf(u) > fabsf(c) * 0x1p-40f);
      const float sc = off ? __uint_as_float(max(__float_as_uint(c) & 0x7f800000u, 8u << 23) - (4u << 23)) : 0.5f * u;
      float upto = fabsf(sc);
#pragma unroll
      for (int o = 2; o < 32; o *= 2) {
        const float z = __shfl_up_sync(0xffffffffu, upto, o);
        if (lane >= o) upto += z;
      }
      const float all = __shfl_sync(0xffffffffu, upto, 30 + (lane & 1));
      const float m = c / all;
      const float grid_ = __uint_as_float((__float_as_uint(2.0625f + 1.03125f * fabsf(m)) & 0x7f800000u) - (7u << 23));
      const float m0 = __fadd_rn(__fadd_rn(m, grid_ * 0x1.8p23f), grid_ * -0x1.8p23f);
      const float rest = fmaf(-m0, all, c);
      float q = (upto - 0.5f * fabsf(sc)) * grid_ < fabsf(rest) ? m0 + copysignf(grid_, rest) : m0;
      if (sc < 0.f) q = -q;
      const int own = 8 * w + g;
      r = __shfl_sync(0xffffffffu, off ? 0.f : v / u, own);
      cq = __shfl_sync(0xffffffffu, pack_bf16(q, q), own);
      swap = __shfl_sync(0xffffffffu, sw, own);
      half2 = __shfl_sync(0xffffffffu, off ? 0u : 0x3f003f00u, own);
      const int odd = (g ^ (g >> 1)) & 1;
#pragma unroll
      for (int i = 0; i < 4; i++)
        bf[i] = (__float_as_uint(__shfl_sync(0xffffffffu, sc, 8 * i + 2 * (lane & 3) + odd)) >> 16) << (16 * odd);
      if (warp == 0) {
        sts128(sb + SCALES + lane * 16, make_uint4(bf[0], bf[1], bf[2], bf[3]));
        asm volatile("bar.arrive 6, 160;" ::: "memory");
      }
    }
    const uint32_t nhalf2 = half2 ^ 0x80008000u, nzero2 = 0x80008000u;
    const uint32_t vec = sb + R_VEC + (16 * w + g) * 2;
    const float b1a = __uint_as_float(half2 << 16) * __uint_as_float(lds16(vec + (swap ? 16 : 0)) << 16);
    const float b1b = __uint_as_float(half2 << 16) * __uint_as_float(lds16(vec + (swap ? 0 : 16)) << 16);
    uint32_t wac[16], wd[16], wbc[16];
    {
      const int mi = lane >> 3, rr = lane & 7;
      const uint32_t a0 = sb + (8 * (mi >> 1) + rr) * 128 + (((2 * w + (mi & 1)) ^ rr) << 4);
#pragma unroll
      for (int ks = 0; ks < 4; ks++) {
        uint32_t A[4], Bm[4], C[4], Dm[4];
        ldsm_x4_t(a0 + ks * 2048 + w1_at(0), A[0], A[1], A[2], A[3]);
        ldsm_x4_t(a0 + ks * 2048 + w1_at(1), Bm[0], Bm[1], Bm[2], Bm[3]);
        ldsm_x4_t(a0 + ks * 2048 + w1_at(2), C[0], C[1], C[2], C[3]);
        ldsm_x4_t(a0 + ks * 2048 + w1_at(3), Dm[0], Dm[1], Dm[2], Dm[3]);
#pragma unroll
        for (int e = 0; e < 4; e++) {
          A[e] = hfma2_bf16(A[e], half2, hfma2_bf16(C[e], half2, nzero2));
          Bm[e] = hfma2_bf16(Bm[e], half2, hfma2_bf16(C[e], nhalf2, nzero2));
          Dm[e] = hfma2_bf16(Dm[e], half2, nzero2);
        }
#pragma unroll
        for (int e = 0; e < 4; e++) {
          wac[4 * ks + e] = swap ? A[e ^ 1] : A[e];
          wbc[4 * ks + e] = swap ? Bm[e ^ 1] : Bm[e];
          wd[4 * ks + e] = swap ? Dm[e ^ 1] : Dm[e];
        }
      }
    }
    asm volatile("fence.proxy.async.shared::cta;" ::: "memory");
    asm volatile("bar.sync 5, %0;" :: "n"(NCW * 128) : "memory");

    const uint32_t lnd = __shfl_sync(0xffffffffu, lane * 4 + ((8 * w + g + (lane & 1) * 32) << 25), lane);
    const uint32_t meta = __shfl_sync(0xffffffffu, g & 1 ? 0xdd8888ddu : 0x88dddd88u, lane);
    const uint32_t zr = grid >> 20;
    const uint32_t sel = keep<K_SEL>(((ring + R_SEL) & 0x3FFFF) >> 4);
    const uint32_t rat = __shfl_sync(0xffffffffu, sums_at(8 * w + (lane & 7)) + (lane >> 3) * 512, lane);
    const uint32_t barid = __shfl_sync(0xffffffffu, 2 + (tid >> 7), lane);
    const uint32_t toff = __shfl_sync(0xffffffffu, (lane & 24) << 1, lane);
    const uint32_t ost = __shfl_sync(0xffffffffu, w * 1024 + sums_at(lane), lane);
    if (active) {
      uint32_t t[8];
      auto load_t = [&](uint32_t ta) {
        ldsm_x4(ta + toff, t[0], t[1], t[2], t[3]);
        ldsm_x4(ta + toff + 64, t[4], t[5], t[6], t[7]);
      };
      load_t(ring + R_TGT0);
      uint32_t hdr = keep<1>(ring), raw, cur = hdr + (R_START - S_EMPTY);
      uint32_t x, nxt;
      auto peek_header = [&]() {
        nxt = hdr & H_NEXT;
        if (K_NX == 1) asm volatile("" : "+r"(nxt));
        x = lds32(nxt + S_HDR);
      };
      auto next_header = [&]() {
        asm volatile("{\n.reg .pred p;\n.reg .u32 n;\n.reg .s32 y;\n"
                     "xor.b32 y, %0, %2;\nsetp.ge.s32 p, y, 0;\n@p bra.uni FRESH;\n"
                     "mov.u32 n, 0;\n"
                     "AGAIN:\nadd.u32 n, n, 1;\nsetp.gt.u32 p, n, 0x1000000;\n@p trap;\nnanosleep.u32 32;\n"
                     "ld.shared.u32 %0, [%1];\nxor.b32 y, %0, %2;\nsetp.lt.s32 p, y, 0;\n@p bra.uni AGAIN;\n"
                     "FRESH:\n}\n" : "+r"(x) : "r"(nxt + S_HDR), "r"(hdr << 1) : "memory");
        if (!K_TOP) raw = __shfl_sync(0xffffffffu, x, 0);
      };
      uint32_t u[8];
      auto gather = [&](auto copy) {
        asm volatile("bar.sync %8, 128;   // %10\n"
                     "ldmatrix.sync.aligned.m8n8.x4.shared.b16 {%0,%1,%2,%3}, [%9];\n"
                     "ldmatrix.sync.aligned.m8n8.x4.shared.b16 {%4,%5,%6,%7}, [%9 + 2048];"
                     : "=r"(u[0]), "=r"(u[1]), "=r"(u[2]), "=r"(u[3]), "=r"(u[4]), "=r"(u[5]), "=r"(u[6]), "=r"(u[7])
                     : "r"(K_BAR ? barid : 2 + wg), "r"(cur + rat), "n"(decltype(copy)::value) : "memory");
      };
      peek_header();
      next_header();
      while (true) {
        __syncwarp();
        if (!(lnd & 0x7c)) mbar_arrive(cur + S_EMPTY);
        cur = K_NX == 2 ? hdr & H_NEXT : nxt;
        hdr = K_TOP ? __shfl_sync(0xffffffffu, x, 0) : raw;
        uint32_t we[16], bq[4];
        {
          float c[4][4];
          asm volatile("mma.sync.aligned.m16n8k16.row.col.f32.bf16.bf16.f32 {%0,%1,%2,%3}, {%4,%5,%6,%7}, {%8,%9}, {%10,%11,%12,%13};"
                       : "=f"(c[0][0]), "=f"(c[0][1]), "=f"(c[0][2]), "=f"(c[0][3])
                       : "r"(wbc[0]), "r"(wbc[1]), "r"(wbc[2]), "r"(wbc[3]), "r"(t[0]), "r"(t[1]), "f"(b1a), "f"(r), "f"(b1b), "f"(__uint_as_float(cq)));
#pragma unroll
          for (int i = 1; i < 4; i++) hmma<true>(c[i], wbc + 4 * i, t[2 * i], t[2 * i + 1]);
#pragma unroll
          for (int i = 0; i < 16; i++) we[i] = hfma2_bf16(t[i >> 1], wd[i], wac[i]);
#pragma unroll
          for (int i = 0; i < 4; i++) bq[i] = pack_bf16(c[i & 2][2 * (i & 1)], c[(i & 2) + 1][2 * (i & 1)]);
        }
        auto chunk = [&](auto groups) {
          constexpr int N8 = decltype(groups)::value, KE = (N8 + 1) / 2, KA = KE - KL;
          float d[4 * N8], o[16];
          uint32_t a[4 * KE];
          auto scores = [&](int i0, int i1) {
#pragma unroll
            for (int i = i0; i < i1; i++) {
              a[2 * i] = i < N8 ? mix(d, i, r) : 0;
              a[2 * i + 1] = i < N8 ? hfma2_bf16(a[2 * i], 0x3f803f80u, cq) : 0;
              if (N8 == 16) {
                uint32_t m = 0x3f803f80u;
                asm volatile("{\n.reg .pred p;\nsetp.ne.u32 p, %1, 0;\n@p ld.shared.u32 %0, [%2];\n}\n"
                             : "+r"(m) : "r"(hdr & H_GENERAL), "r"(cur + S_MASK + i * 16 + (lnd & 12)) : "memory");
                a[2 * i] = hfma2_bf16(a[2 * i], m, 0x80008000u);
                a[2 * i + 1] = hfma2_bf16(a[2 * i + 1], m, 0x80008000u);
              }
            }
          };
          const uint32_t lo = cur >> 4, lo1 = lo + 0x10000, lo2 = lo + K_LO2 * 0x10000;
          const uint32_t hi1 = DESC_ROWS + (K_HI1 == 1 ? cur >> 24 : lo >> 19);
          const uint32_t hi2 = K_HI2 == 1 ? DESC_HALVES + (cur >> 24) : hi1 + (DESC_HALVES - DESC_ROWS);
          auto g2 = [&](int k) {
            if (k == 0) g2_first(o, a, lo2, meta, hi2); else g2_more(o, a + 4 * k, lo2 + 128 * k, meta, hi2);
          };
          uint32_t oa = cur + ost;
          mma_fence();
          g1_bias<NA>(d, bq, sel);
          g1_bias<N8 - NA>(d + 4 * NA, bq, sel);
          mma_commit();
          mbar_wait(cur + S_FULL, hdr >> 31);
          mma_fence();
#pragma unroll
          for (int k = 0; k < 4; k++) g1_step<NA>(d, we + 4 * k, lo1 + 2 * k, hi1);
          mma_commit();
#pragma unroll
          for (int k = 0; k < 4; k++) g1_step<N8 - NA>(d + 4 * NA, we + 4 * k, lo1 + 64 * NA + 2 * k, hi1);
          mma_commit();
          mma_wait<1>(d, Int<NA>());
          tanh_some(d, 0, 4 * NA);
          scores(0, S0);
          cut_here(oa, zr);
          mma_wait<0>(d + 4 * NA, Int<N8 - NA>());
          load_t(cur + S_TGT);
          peek_header();
          tanh_some(d, 4 * NA, 8 * KA + D0);
          scores(S0, 2 * KA);
          mma_fence();
#pragma unroll
          for (int k = 0; k < KA; k++) {
            g2(k);
            if (k == KA - KC) cut_here(oa, zr);
          }
          mma_commit();
          tanh_some(d, 8 * KA + D0, 4 * N8);
          scores(2 * KA, 2 * KE);
          mma_fence();
#pragma unroll
          for (int k = KA; k < KE; k++) g2(k);
          mma_commit();
          next_header();
          mma_wait<0>(o, Int<4>());
#pragma unroll
          for (int e = 0; e < 2; e++)
            stsm_x4_t(oa + e * 512, pack_bf16(o[2 * e], o[2 * e + 1]), pack_bf16(o[2 * e + 4], o[2 * e + 5]),
                      pack_bf16(o[2 * e + 8], o[2 * e + 9]), pack_bf16(o[2 * e + 12], o[2 * e + 13]));
        };
        if (hdr & H_13) { chunk(Int<13>()); if (hdr & (H_FINAL | H_12)) { gather(Int<0>()); break; } }
        else if (hdr & H_12) { chunk(Int<12>()); if (hdr & (H_FINAL | H_14)) { gather(Int<1>()); break; } }
        else if (hdr & H_14) { chunk(Int<14>()); if (hdr & (H_FINAL | H_15)) { gather(Int<2>()); break; } }
        else if (hdr & H_15) { chunk(Int<15>()); if (hdr & (H_FINAL | H_16)) { gather(Int<3>()); break; } }
        else {
          asm volatile("{\n.reg .pred p;\nsetp.ne.u32 p, %0, 0;\n@p exit;\n}\n" :: "r"(hdr & H_STOP) : "memory");
          chunk(Int<16>());
          if (hdr & H_FINAL) { gather(Int<4>()); break; }
        }
      }
      float c[4], e[4];
      hmma<true>(c, u, bf[0], bf[1]);
      hmma<true>(e, u + 4, bf[2], bf[3]);
      const char* dst = reinterpret_cast<const char*>(out) + (uint64_t)(x * 2) * kD + (lnd >> 24);
      asm volatile("st.global.u16 [%0], %1;"
                   :: "l"(dst), "h"(__bfloat16_as_ushort(__float2bfloat16((c[0] + c[3]) + (e[0] + e[3])))) : "memory");
      asm volatile("exit;");
    }
  } else {
    const int pw = warp - NCW * 4;
    const uint32_t ring = sb + pw * RING_BYTES;
    asm volatile("setmaxnreg.dec.sync.aligned.u32 %0;" :: "n"(PROD_REGS));
    if (pw < NCW) {
      int b = pw * grid + cta, bn = b + bstep;
      uint4 mw = load_mask(mask, min(b, B - 1), min(lane, 24));
      if (lane == 0) {
#pragma unroll
        for (int i = 0; i < NSLOT; i++) {
          mbar_init(ring + i * SLOT_BYTES + S_FULL, 34);
          mbar_init(ring + i * SLOT_BYTES + S_EMPTY, 4);
          mbar_arrive(ring + i * SLOT_BYTES + S_FULL);
          sts32(ring + i * SLOT_BYTES + S_HDR, 0x80000000u);
        }
        mbar_init(ring + R_START, 4);
        sts32(ring + R_STOP, pw < ACT ? 0 : ring);
      }
      sts32(sb + R_PACE + lane * 4, 0);
      asm volatile("bar.arrive 1, %0;" :: "n"(NCW * 160) : "memory");
      asm volatile("bar.arrive 6, 160;" ::: "memory");
      if (pw >= ACT) return;
      const uint32_t list = ring + R_LIST;
      uint32_t lt;
      asm("mov.u32 %0, %%lanemask_lt;" : "=r"(lt));
      const uint32_t ln = __shfl_sync(0xffffffffu, lane, lane);
      const uint32_t r4 = (ln >> 3) * 4, c16 = (ln & 7) * 16, l25 = min(ln, 24u);
      const uint32_t pick = ln < 25 ? 0xeca8 : 0x9999;
      uint32_t dst[4];
#pragma unroll
      for (int i = 0; i < 4; i++) dst[i] = ring + (r4 + i) * 128 + (c16 ^ (((r4 + i) & 7) << 4));
      uint64_t pol;
      asm("createpolicy.fractional.L2::evict_first.b64 %0, 1.0;" : "=l"(pol));
      uint32_t sa = ring, phase = 1;
      const uint32_t wrap = (uint32_t)(max(B - NSTATIC * bstep, 0) + bstep - 1);
      auto next_slot = [&]() {
        const bool wrapped = sa == ring + (NSLOT - 1) * SLOT_BYTES;
        const int step = wrapped ? -(NSLOT - 1) * SLOT_BYTES : SLOT_BYTES;
        sa += step;
        phase ^= wrapped;
#pragma unroll
        for (int i = 0; i < 4; i++) dst[i] += step;
      };
      uint32_t claimer = ln;
      uint32_t drawn;
      auto draw = [&]() {
        drawn = B;
        asm volatile("{\n.reg .pred p;\nsetp.eq.u32 p, %3, 0;\n@p atom.global.inc.u32 %0, [%1], %2;\n}\n"
                     : "+r"(drawn) : "l"(counter), "r"(wrap), "r"(claimer) : "memory");
      };
      if (b >= B) draw();
      int n = kL, mean16 = 8 * kL;
      while (b < B) {
        const uint32_t e0 = nonzero_as_one(mw.x), e1 = nonzero_as_one(mw.y);
        const uint32_t e2 = nonzero_as_one(mw.z), e3 = nonzero_as_one(mw.w);
        const uint32_t nonbin = (e0 ^ mw.x) | (e1 ^ mw.y) | (e2 ^ mw.z) | (e3 ^ mw.w);
        const uint32_t sA = prmt(e0, e1, pick), sB = prmt(e2, e3, pick);
        const uint32_t pA = (sA & 0x01010101u) * 0x01010101u;
        const uint32_t pB = ((sB & 0x01010101u) + (pA >> 24)) * 0x01010101u;
        uint32_t pos = 0;
        n = 0;
#pragma unroll
        for (int k = 0; k < 4; k++) {
          const uint32_t bal = ballot_bit(pB, 0x01000000u << k);
          pos += __popc(bal & lt) << k;
          n += __popc(bal) << k;
        }
        const uint32_t general = __any_sync(0xffffffffu, nonbin != 0);
        const uint32_t aA = (pA + pos * 0x01010101u) | ~sA, aB = (pB + pos * 0x01010101u) | ~sB;
#pragma unroll
        for (int i = 0; i < 8; i++) sts8(list - 1 + prmt(i < 4 ? aA : aB, 0, 0x4440 + (i & 3)), 8 * ln + i);
        __syncwarp();

        const uint64_t src = reinterpret_cast<uint64_t>(hist) + (uint64_t)b * (kL * kD * 2);
        const bool no_carry = (uint32_t)src <= 0xffffffffu - kL * kD * 2;
        auto begin_fill = [&](uint32_t h, uint32_t part, int nc, int bt, auto extra) {
          mbar_wait(sa + S_EMPTY, phase);
          if (bt >= B && !part) h |= H_FINAL;
          extra();
          {
            const bool wrapped = sa == ring + (NSLOT - 1) * SLOT_BYTES;
            sts32(sa + S_HDR, (h | (wrapped ? ring + 0x40000000u : sa + SLOT_BYTES)) ^ ((phase - 1) & 0xc0000000u));
          }
          sts32(sa + S_ROW + phase * 4, b | part);
          asm volatile("{\n.reg .pred p;\nsetp.eq.u32 p, %1, 0;\n@p mbarrier.arrive.shared::cta.b64 _, [%0];\n}\n"
                       :: "r"(sa + S_FULL), "r"(ln) : "memory");
          mean16 += nc - (mean16 >> 4);
          asm volatile("{\n.reg .u32 f, c;\n.reg .s32 d;\n.reg .pred p;\n"
                       "mov.u32 c, %%globaltimer_lo;\n"
                       "red.shared.max.u32 [%0], c;\n"
                       "atom.shared.add.u32 f, [%0], %1;\n"
                       "shfl.sync.idx.b32 f, f, 0, 31, 0xffffffff;\n"
                       "SPIN:\n"
                       "mov.u32 c, %%globaltimer_lo;\n"
                       "sub.s32 d, c, f;\n"
                       "setp.gt.u32 p, d, %2;\n"
                       "@p bra.uni SPIN;\n}\n" :: "r"(sb + R_PACE + ln * 4), "r"((bn >= slow_from ? mean16 * slow_pace : nc * pace16) >> 8), "r"(~(pace16 * (CHUNK / 64))) : "memory");
          if (!(part & ROW_REST)) {
            mw = load_mask(mask, min(bn, B - 1), l25);
            draw();
          }
          asm volatile("cp.async.ca.shared.global [%0], [%1], 4;"
                       :: "r"(sa + S_TGT + ln * 4), "l"(reinterpret_cast<const uint32_t*>(target) + ((uint32_t)min(bt, B - 1) * 32u + ln)) : "memory");
        };
        auto end_fill = [&](int nc) {
          cp_async_arrive_noinc(sa + S_FULL);
          next_slot();
        };
        auto usual = [&]() {
          uint32_t idx[7];
#pragma unroll
          for (int t = 0; t < 7; t++) idx[t] = lds32(list + r4 + t * 16);
          begin_fill(size_flag(n), 0, n, bn, [](){});
          const int left = n - r4;
          const uint32_t base = (uint32_t)src + c16;
          uint64_t a = (uint64_t)((uint32_t)(src >> 32) + (ln >> 5)) << 32;
          cp_group<0, false>(dst, a, idx[0], base, left, pol);
          cp_group<1, false>(dst, a, idx[1], base, left, pol);
          cp_group<2, false>(dst, a, idx[2], base, left, pol);
          cp_group<3, false>(dst, a, idx[3], base, left, pol);
          cp_group<4, true>(dst, a, idx[4], base, left, pol);
          cp_group<5, true>(dst, a, idx[5], base, left, pol);
          if (n > 96) {
            cp_group<6, true>(dst, a, idx[6], base, left, pol);
            if (n > 112) cp_group<7, true>(dst, a, lds32(list + r4 + 112), base, left, pol);
          }
          end_fill(n);
        };
        auto other = [&]() {
          int r0 = 0, nc = n <= CHUNK ? n : n <= 160 ? 64 : 96;
#pragma unroll 1
          do {
            const bool more = r0 + nc < n;
            begin_fill(general ? H_GENERAL : size_flag(max(nc, 64)), (more ? ROW_MORE : 0u) | (r0 ? ROW_REST : 0u), nc, more ? b : bn, [&]() {
#pragma unroll 1
              for (int z = ln; general && z < CHUNK; z += 32) {
                uint32_t v = 0;
                if (z < nc) {
                  uint32_t row;
                  asm volatile("ld.shared.u8 %0, [%1];" : "=r"(row) : "r"(list + r0 + z) : "memory");
                  v = __bfloat16_as_ushort(mask[(size_t)b * kL + row]);
                }
                sts16(sa + S_MASK + z * 2, v);
              }
              __syncwarp();
            });
            uint32_t rows4 = lds32(list + r0 + r4);
#pragma unroll 1
            for (int z = 0; z < CHUNK; z += 16) {
              const uint32_t now = rows4;
              rows4 = lds32(list + r0 + r4 + z + 16);
#pragma unroll
              for (int i = 0; i < 4; i++)
                asm volatile("{\n.reg .pred p;\nsetp.ge.s32 p, %2, %3;\ncp.async.cg.shared.global [%0], [%1], 16, p;\n}\n"
                             :: "r"(dst[i] + z * 128), "l"(src + c16 + prmt(now, 0, 0x4440 + i) * 128), "r"(z + r4 + i), "r"(nc) : "memory");
            }
            end_fill(nc);
            r0 += nc;
            nc = n - nc;
          } while (r0 < n);
        };
        if (n < 64 || n > CHUNK || !no_carry || general) other(); else usual();
        if (bn >= B) break;
        b = bn;
        bn = __shfl_sync(0xffffffffu, drawn, 0) + NSTATIC * bstep;
        if (bn >= B) claimer = 1;
      }
      if (b < B) mbar_wait(ring + R_START, 0);
      sts32(sa + S_HDR, (n <= CHUNK ? b : H_STOP) | (phase ^ 1) << 31);
      if (n <= CHUNK) {
#pragma unroll 1
        for (int i = 1; i < 2 * NSLOT; i++) next_slot();
      }
      sts32(ring + R_STOP, sa + (phase ^ 1));
      asm volatile("cp.async.wait_all;" ::: "memory");
    } else {
      uint32_t due = clock();
      int s0 = NSTATIC * bstep + (PF_EARLY * grid + cta) * PF_ROWS;
      auto prefetch = [&]() {
        const int cnt = min(PF_ROWS, B - s0);
        if (lane == 0) {
          prefetch_l2(mask + (size_t)s0 * kL, cnt * kL * 2);
          prefetch_l2(target + (size_t)s0 * kD, cnt * kD * 2);
        }
        s0 += grid * PF_ROWS;
      };
#pragma unroll 1
      for (int j = PF_EARLY; j < PF_FAST && s0 < B; j++) {
        while ((int)(due - (uint32_t)clock()) > 0) {}
        prefetch();
        due += PF_CYCLES;
      }
      due += (PF_FAST - 1) * PF_SLOW - (PF_FAST - PF_EARLY) * PF_CYCLES + (cta & 255) * (PF_SLOW / 256);
      asm volatile("bar.sync 6, 160;" ::: "memory");
      constexpr uint32_t WHERE = 0x3ffff;
      const uint32_t mine = __shfl_sync(0xffffffffu, sb + min(lane, NCW - 1) * RING_BYTES, lane);
      uint32_t at = mine | ~WHERE;
      const uint32_t ln = __shfl_sync(0xffffffffu, lane, lane);
      const uint32_t rd = __shfl_sync(0xffffffffu, sums_at(2 * (lane & 7)) + (lane >> 3) * 512, lane);
      uint4 bf = lds128(sb + SCALES + lane * 16);
      bf.x += grid >> 20;
      bf.z += grid >> 20;
      uint32_t* const dst = reinterpret_cast<uint32_t*>(out) + ((lane & 1) * 16 + (lane & 2) * 4 + (lane >> 2));
      uint32_t idle = 0;
#pragma unroll 1
      while (true) {
        const uint32_t go = __reduce_max_sync(0xffffffffu, mbar_test((at & (WHERE - 1)) + S_EMPTY, at & 1) ? at : 0u);
        if (go) {
          const uint32_t sa = go & (WHERE - 1);
          const uint32_t row = lds32(sa + S_ROW + 4 - (go & 1) * 4);
          uint32_t u[8][4];
#pragma unroll
          for (int i = 0; i < 8; i++) ldsm_x4(((sa + rd) ^ (i & 1) * 16) + (i & 2) * 128 + (i >> 2) * 2048, u[i][0], u[i][1], u[i][2], u[i][3]);
          cut_here(idle, sa == 0);
          float c[4][4];
#pragma unroll
          for (int j = 0; j < 4; j++) hmma<true>(c[j], u[j], bf.x, bf.y);
#pragma unroll
          for (int j = 0; j < 4; j++) hmma<false>(c[j], u[4 + j], bf.z, bf.w);
          float e0 = c[0][0] + c[0][3], e1 = c[1][0] + c[1][3];
          if (ln & 2) { e0 = c[2][0] + c[2][3]; e1 = c[3][0] + c[3][3]; }
          __syncwarp();
          if (ln == 0) mbar_arrive(sa + S_FULL);
          if (at == go) at = (sa == mine + (NSLOT - 1) * SLOT_BYTES ? (at - (NSLOT - 1) * SLOT_BYTES) ^ 1 : at + SLOT_BYTES) - (WHERE + 1);
          if (__builtin_expect(row >= ROW_REST, 0)) {
            const uint32_t carry = __reduce_max_sync(0xffffffffu, mine <= sa ? mine : 0u) + R_CARRY + ln * 8;
            if (row & ROW_REST) { e0 += __uint_as_float(lds32(carry)); e1 += __uint_as_float(lds32(carry + 4)); }
            sts32(carry, __float_as_uint(e0));
            sts32(carry + 4, __float_as_uint(e1));
          }
          if (row < ROW_MORE) dst[(row & (ROW_REST - 1)) * 32] = pack_bf16(e0, e1);
        } else {
          if (__all_sync(0xffffffffu, lds32(mine + R_STOP) == (at & WHERE))) break;
          if (++idle > 0x4000000) __trap();
          if (s0 < B && (int)(due - (uint32_t)clock()) <= 0) { prefetch(); due += PF_SLOW; }
          if (RED_SLEEP) __nanosleep(RED_SLEEP);
        }
      }
    }
  }
}

}

extern "C" void kernel_launch(void* const* d_in, const int* in_sizes, int n_in, void* d_out, int out_size) {
  const __nv_bfloat16* target = (const __nv_bfloat16*)d_in[0];
  const __nv_bfloat16* hist = (const __nv_bfloat16*)d_in[1];
  const __nv_bfloat16* mask = (const __nv_bfloat16*)d_in[2];
  const __nv_bfloat16* w1 = (const __nv_bfloat16*)d_in[3];
  const __nv_bfloat16* b1 = (const __nv_bfloat16*)d_in[4];
  const __nv_bfloat16* w2 = (const __nv_bfloat16*)d_in[5];
  const __nv_bfloat16* b2 = (const __nv_bfloat16*)d_in[6];
  const int B = in_sizes[0] / din::kD;
  if (B <= 0) return;
  constexpr int early_rows = din::NSTATIC * NCW + PF_EARLY * PF_ROWS;
  constexpr int pf_mask = (early_rows * din::kL * 2 + din::NTHREADS - 1) / din::NTHREADS;
  constexpr int pf_tgt = (early_rows * din::kD * 2 + din::NTHREADS - 1) / din::NTHREADS;
  static int sms = 0, pace = 0;
  static unsigned int* counter = nullptr;
  if (sms == 0) {
    int dev = 0, khz = 0, bits = 0;
    cudaGetDevice(&dev);
    cudaDeviceGetAttribute(&sms, cudaDevAttrMultiProcessorCount, dev);
    cudaDeviceGetAttribute(&khz, cudaDevAttrMemoryClockRate, dev);
    cudaDeviceGetAttribute(&bits, cudaDevAttrGlobalMemoryBusWidth, dev);
    if (khz > 0 && bits > 0) pace = (int)(16.0 * 128.0 * sms / (khz * 1e-6 * 2.0 * bits / 8.0));
    if (pace > 256) pace = 0;
    cudaGetSymbolAddress((void**)&counter, din::g_next);
    cudaFuncSetAttribute(din::din_kernel<0, 0>, cudaFuncAttributeMaxDynamicSharedMemorySize, din::SMEM_BYTES);
    cudaFuncSetAttribute(din::din_kernel<pf_mask, pf_tgt>, cudaFuncAttributeMaxDynamicSharedMemorySize, din::SMEM_BYTES);
  }
  const bool early = (long long)pf_mask * din::NTHREADS * sms <= (long long)B * din::kL * 2 &&
                     (long long)pf_tgt * din::NTHREADS * sms <= (long long)B * din::kD * 2;
  (early ? din::din_kernel<pf_mask, pf_tgt> : din::din_kernel<0, 0>)<<<sms, din::NTHREADS, din::SMEM_BYTES>>>(
      mask, target, B, sms, w1, hist, b1, w2, b2, (__nv_bfloat16*)d_out, counter, pace * 16,
      pace + pace * SLOW_BY / 80, B - SLOW_ROUNDS * NCW * sms);
}
```

```cpp
#include <cuda_runtime.h>
#include <cuda_bf16.h>
#include <stdint.h>

namespace din {

constexpr int kL = 200, kD = 64;
#define NCW 3
#define NSLOT 3
constexpr int CHUNK = 128;
constexpr int NTHREADS = NCW * 128 + 128;
#define PREGS 56
#define CREGS 152
constexpr int PROD_REGS = PREGS, CONS_REGS = CREGS;
#define PF_ROWS 8
#define PF_FAST 10
#define PF_SLOW 2000
#define PF_CYCLES 280
#define RED_SLEEP 100
#define K_SEL 1
#define K_LO2 2
#define K_HI1 2
#define K_HI2 2
#define K_NX 2
#define K_BAR 1
#define K_TOP 1
#define NA 4
#define KL 2
#define S0 1
#define D0 5
#define KC 4
#define PF_EARLY 3
#define SLOW_ROUNDS 5
#define SLOW_BY 13
constexpr int NSTATIC = 2;
constexpr int S_TGT = CHUNK * 128;
constexpr int S_HDR = S_TGT + 128;
constexpr int S_FULL = S_HDR + 8;
constexpr int S_EMPTY = S_HDR + 16;
constexpr int S_ROW = S_HDR + 24;
constexpr int S_MASK = S_TGT + 256;
constexpr int S_OUT = S_TGT + 1024;
constexpr int SLOT_BYTES = S_OUT + 4096;
constexpr int RING_BYTES_ = NSLOT * SLOT_BYTES;
constexpr int R_PACE = 2 * RING_BYTES_ + S_TGT + 768;
constexpr int R_START = S_HDR + 32;
constexpr int R_STOP = S_HDR + 44;
constexpr int R_LIST = S_TGT + 512;
constexpr int R_VEC = S_TGT + 768;
constexpr int R_SEL = S_TGT + 896;
constexpr int R_CARRY = SLOT_BYTES + S_TGT + 512;
constexpr int R_TGT0 = (NSLOT - 1) * SLOT_BYTES + S_OUT;
constexpr int RING_BYTES = NSLOT * SLOT_BYTES;
constexpr int SCALES = NCW * RING_BYTES + 32768;
constexpr int SMEM_BYTES = SCALES + 512 + 1024;
__device__ constexpr int w1_at(int i) { return NCW * RING_BYTES + i * 8192; }
static_assert(SMEM_BYTES <= 232448, "shared memory");
constexpr uint32_t H_12 = 0x1f, H_13 = 0x20, H_14 = 0x40, H_15 = 0x80, H_16 = 0x100;
constexpr uint32_t H_GENERAL = 1u << 18, H_FINAL = 1u << 19, H_STOP = 1u << 20, H_NEXT = 0x3fc3fc00;
__device__ __forceinline__ uint32_t size_flag(int rows) { return 1u << ((rows - 57) >> 3); }
constexpr uint32_t ROW_REST = 1u << 30, ROW_MORE = 1u << 31;

__device__ unsigned int g_next;

#define STR2(x) #x
#define STR(x) STR2(x)
template<int V> struct Int { static constexpr int value = V; };
template<int G> __device__ __forceinline__ void g1_bias(float* d, const uint32_t (&bq)[4], uint32_t loSel);
template<int G> __device__ __forceinline__ void g1_step(float* d, const uint32_t* a, uint32_t loH, uint32_t hiH);
template<> __device__ __forceinline__ void g1_bias<4>(float* d, const uint32_t (&bq)[4], uint32_t loSel) {
  asm volatile("{\n.reg .b64 db;\n.reg .b32 zr;\n"
    "mov.b32 zr, 0;\nmov.b64 db, {%20, zr};\n"
    "wgmma.mma_async.sync.aligned.m64n32k16.f32.bf16.bf16 {%0, %1, %2, %3, %4, %5, %6, %7, %8, %9, %10, %11, %12, %13, %14, %15}, {%16, %17, %18, %19}, db, 0, 1, 1, 0;\n}\n"
    : "=f"(d[0]), "=f"(d[1]), "=f"(d[2]), "=f"(d[3]), "=f"(d[4]), "=f"(d[5]), "=f"(d[6]), "=f"(d[7]), "=f"(d[8]), "=f"(d[9]), "=f"(d[10]), "=f"(d[11]), "=f"(d[12]), "=f"(d[13]), "=f"(d[14]), "=f"(d[15])
    : "r"(bq[0]), "r"(bq[1]), "r"(bq[2]), "r"(bq[3]), "r"(loSel)
    : "memory");
}
template<> __device__ __forceinline__ void g1_bias<8>(float* d, const uint32_t (&bq)[4], uint32_t loSel) {
  asm volatile("{\n.reg .b64 db;\n.reg .b32 zr;\n"
    "mov.b32 zr, 0;\nmov.b64 db, {%36, zr};\n"
    "wgmma.mma_async.sync.aligned.m64n64k16.f32.bf16.bf16 {%0, %1, %2, %3, %4, %5, %6, %7, %8, %9, %10, %11, %12, %13, %14, %15, %16, %17, %18, %19, %20, %21, %22, %23, %24, %25, %26, %27, %28, %29, %30, %31}, {%32, %33, %34, %35}, db, 0, 1, 1, 0;\n}\n"
    : "=f"(d[0]), "=f"(d[1]), "=f"(d[2]), "=f"(d[3]), "=f"(d[4]), "=f"(d[5]), "=f"(d[6]), "=f"(d[7]), "=f"(d[8]), "=f"(d[9]), "=f"(d[10]), "=f"(d[11]), "=f"(d[12]), "=f"(d[13]), "=f"(d[14]), "=f"(d[15]), "=f"(d[16]), "=f"(d[17]), "=f"(d[18]), "=f"(d[19]), "=f"(d[20]), "=f"(d[21]), "=f"(d[22]), "=f"(d[23]), "=f"(d[24]), "=f"(d[25]), "=f"(d[26]), "=f"(d[27]), "=f"(d[28]), "=f"(d[29]), "=f"(d[30]), "=f"(d[31])
    : "r"(bq[0]), "r"(bq[1]), "r"(bq[2]), "r"(bq[3]), "r"(loSel)
    : "memory");
}
template<> __device__ __forceinline__ void g1_bias<9>(float* d, const uint32_t (&bq)[4], uint32_t loSel) {
  asm volatile("{\n.reg .b64 db;\n.reg .b32 zr;\n"
    "mov.b32 zr, 0;\nmov.b64 db, {%40, zr};\n"
    "wgmma.mma_async.sync.aligned.m64n72k16.f32.bf16.bf16 {%0, %1, %2, %3, %4, %5, %6, %7, %8, %9, %10, %11, %12, %13, %14, %15, %16, %17, %18, %19, %20, %21, %22, %23, %24, %25, %26, %27, %28, %29, %30, %31, %32, %33, %34, %35}, {%36, %37, %38, %39}, db, 0, 1, 1, 0;\n}\n"
    : "=f"(d[0]), "=f"(d[1]), "=f"(d[2]), "=f"(d[3]), "=f"(d[4]), "=f"(d[5]), "=f"(d[6]), "=f"(d[7]), "=f"(d[8]), "=f"(d[9]), "=f"(d[10]), "=f"(d[11]), "=f"(d[12]), "=f"(d[13]), "=f"(d[14]), "=f"(d[15]), "=f"(d[16]), "=f"(d[17]), "=f"(d[18]), "=f"(d[19]), "=f"(d[20]), "=f"(d[21]), "=f"(d[22]), "=f"(d[23]), "=f"(d[24]), "=f"(d[25]), "=f"(d[26]), "=f"(d[27]), "=f"(d[28]), "=f"(d[29]), "=f"(d[30]), "=f"(d[31]), "=f"(d[32]), "=f"(d[33]), "=f"(d[34]), "=f"(d[35])
    : "r"(bq[0]), "r"(bq[1]), "r"(bq[2]), "r"(bq[3]), "r"(loSel)
    : "memory");
}
template<> __device__ __forceinline__ void g1_bias<10>(float* d, const uint32_t (&bq)[4], uint32_t loSel) {
  asm volatile("{\n.reg .b64 db;\n.reg .b32 zr;\n"
    "mov.b32 zr, 0;\nmov.b64 db, {%44, zr};\n"
    "wgmma.mma_async.sync.aligned.m64n80k16.f32.bf16.bf16 {%0, %1, %2, %3, %4, %5, %6, %7, %8, %9, %10, %11, %12, %13, %14, %15, %16, %17, %18, %19, %20, %21, %22, %23, %24, %25, %26, %27, %28, %29, %30, %31, %32, %33, %34, %35, %36, %37, %38, %39}, {%40, %41, %42, %43}, db, 0, 1, 1, 0;\n}\n"
    : "=f"(d[0]), "=f"(d[1]), "=f"(d[2]), "=f"(d[3]), "=f"(d[4]), "=f"(d[5]), "=f"(d[6]), "=f"(d[7]), "=f"(d[8]), "=f"(d[9]), "=f"(d[10]), "=f"(d[11]), "=f"(d[12]), "=f"(d[13]), "=f"(d[14]), "=f"(d[15]), "=f"(d[16]), "=f"(d[17]), "=f"(d[18]), "=f"(d[19]), "=f"(d[20]), "=f"(d[21]), "=f"(d[22]), "=f"(d[23]), "=f"(d[24]), "=f"(d[25]), "=f"(d[26]), "=f"(d[27]), "=f"(d[28]), "=f"(d[29]), "=f"(d[30]), "=f"(d[31]), "=f"(d[32]), "=f"(d[33]), "=f"(d[34]), "=f"(d[35]), "=f"(d[36]), "=f"(d[37]), "=f"(d[38]), "=f"(d[39])
    : "r"(bq[0]), "r"(bq[1]), "r"(bq[2]), "r"(bq[3]), "r"(loSel)
    : "memory");
}
template<> __device__ __forceinline__ void g1_bias<11>(float* d, const uint32_t (&bq)[4], uint32_t loSel) {
  asm volatile("{\n.reg .b64 db;\n.reg .b32 zr;\n"
    "mov.b32 zr, 0;\nmov.b64 db, {%48, zr};\n"
    "wgmma.mma_async.sync.aligned.m64n88k16.f32.bf16.bf16 {%0, %1, %2, %3, %4, %5, %6, %7, %8, %9, %10, %11, %12, %13, %14, %15, %16, %17, %18, %19, %20, %21, %22, %23, %24, %25, %26, %27, %28, %29, %30, %31, %32, %33, %34, %35, %36, %37, %38, %39, %40, %41, %42, %43}, {%44, %45, %46, %47}, db, 0, 1, 1, 0;\n}\n"
    : "=f"(d[0]), "=f"(d[1]), "=f"(d[2]), "=f"(d[3]), "=f"(d[4]), "=f"(d[5]), "=f"(d[6]), "=f"(d[7]), "=f"(d[8]), "=f"(d[9]), "=f"(d[10]), "=f"(d[11]), "=f"(d[12]), "=f"(d[13]), "=f"(d[14]), "=f"(d[15]), "=f"(d[16]), "=f"(d[17]), "=f"(d[18]), "=f"(d[19]), "=f"(d[20]), "=f"(d[21]), "=f"(d[22]), "=f"(d[23]), "=f"(d[24]), "=f"(d[25]), "=f"(d[26]), "=f"(d[27]), "=f"(d[28]), "=f"(d[29]), "=f"(d[30]), "=f"(d[31]), "=f"(d[32]), "=f"(d[33]), "=f"(d[34]), "=f"(d[35]), "=f"(d[36]), "=f"(d[37]), "=f"(d[38]), "=f"(d[39]), "=f"(d[40]), "=f"(d[41]), "=f"(d[42]), "=f"(d[43])
    : "r"(bq[0]), "r"(bq[1]), "r"(bq[2]), "r"(bq[3]), "r"(loSel)
    : "memory");
}
template<> __device__ __forceinline__ void g1_bias<12>(float* d, const uint32_t (&bq)[4], uint32_t loSel) {
  asm volatile("{\n.reg .b64 db;\n.reg .b32 zr;\n"
    "mov.b32 zr, 0;\nmov.b64 db, {%52, zr};\n"
    "wgmma.mma_async.sync.aligned.m64n96k16.f32.bf16.bf16 {%0, %1, %2, %3, %4, %5, %6, %7, %8, %9, %10, %11, %12, %13, %14, %15, %16, %17, %18, %19, %20, %21, %22, %23, %24, %25, %26, %27, %28, %29, %30, %31, %32, %33, %34, %35, %36, %37, %38, %39, %40, %41, %42, %43, %44, %45, %46, %47}, {%48, %49, %50, %51}, db, 0, 1, 1, 0;\n}\n"
    : "=f"(d[0]), "=f"(d[1]), "=f"(d[2]), "=f"(d[3]), "=f"(d[4]), "=f"(d[5]), "=f"(d[6]), "=f"(d[7]), "=f"(d[8]), "=f"(d[9]), "=f"(d[10]), "=f"(d[11]), "=f"(d[12]), "=f"(d[13]), "=f"(d[14]), "=f"(d[15]), "=f"(d[16]), "=f"(d[17]), "=f"(d[18]), "=f"(d[19]), "=f"(d[20]), "=f"(d[21]), "=f"(d[22]), "=f"(d[23]), "=f"(d[24]), "=f"(d[25]), "=f"(d[26]), "=f"(d[27]), "=f"(d[28]), "=f"(d[29]), "=f"(d[30]), "=f"(d[31]), "=f"(d[32]), "=f"(d[33]), "=f"(d[34]), "=f"(d[35]), "=f"(d[36]), "=f"(d[37]), "=f"(d[38]), "=f"(d[39]), "=f"(d[40]), "=f"(d[41]), "=f"(d[42]), "=f"(d[43]), "=f"(d[44]), "=f"(d[45]), "=f"(d[46]), "=f"(d[47])
    : "r"(bq[0]), "r"(bq[1]), "r"(bq[2]), "r"(bq[3]), "r"(loSel)
    : "memory");
}
template<> __device__ __forceinline__ void g1_step<4>(float* d, const uint32_t* a, uint32_t loH, uint32_t hiH) {
  asm volatile("{\n.reg .b64 db;\nmov.b64 db, {%20, %21};\n"
    "wgmma.mma_async.sync.aligned.m64n32k16.f32.bf16.bf16 {%0, %1, %2, %3, %4, %5, %6, %7, %8, %9, %10, %11, %12, %13, %14, %15}, {%16, %17, %18, %19}, db, 1, 1, 1, 0;\n}\n"
    : "+f"(d[0]), "+f"(d[1]), "+f"(d[2]), "+f"(d[3]), "+f"(d[4]), "+f"(d[5]), "+f"(d[6]), "+f"(d[7]), "+f"(d[8]), "+f"(d[9]), "+f"(d[10]), "+f"(d[11]), "+f"(d[12]), "+f"(d[13]), "+f"(d[14]), "+f"(d[15])
    : "r"(a[0]), "r"(a[1]), "r"(a[2]), "r"(a[3]), "r"(loH), "r"(hiH)
    : "memory");
}
template<> __device__ __forceinline__ void g1_step<8>(float* d, const uint32_t* a, uint32_t loH, uint32_t hiH) {
  asm volatile("{\n.reg .b64 db;\nmov.b64 db, {%36, %37};\n"
    "wgmma.mma_async.sync.aligned.m64n64k16.f32.bf16.bf16 {%0, %1, %2, %3, %4, %5, %6, %7, %8, %9, %10, %11, %12, %13, %14, %15, %16, %17, %18, %19, %20, %21, %22, %23, %24, %25, %26, %27, %28, %29, %30, %31}, {%32, %33, %34, %35}, db, 1, 1, 1, 0;\n}\n"
    : "+f"(d[0]), "+f"(d[1]), "+f"(d[2]), "+f"(d[3]), "+f"(d[4]), "+f"(d[5]), "+f"(d[6]), "+f"(d[7]), "+f"(d[8]), "+f"(d[9]), "+f"(d[10]), "+f"(d[11]), "+f"(d[12]), "+f"(d[13]), "+f"(d[14]), "+f"(d[15]), "+f"(d[16]), "+f"(d[17]), "+f"(d[18]), "+f"(d[19]), "+f"(d[20]), "+f"(d[21]), "+f"(d[22]), "+f"(d[23]), "+f"(d[24]), "+f"(d[25]), "+f"(d[26]), "+f"(d[27]), "+f"(d[28]), "+f"(d[29]), "+f"(d[30]), "+f"(d[31])
    : "r"(a[0]), "r"(a[1]), "r"(a[2]), "r"(a[3]), "r"(loH), "r"(hiH)
    : "memory");
}
template<> __device__ __forceinline__ void g1_step<9>(float* d, const uint32_t* a, uint32_t loH, uint32_t hiH) {
  asm volatile("{\n.reg .b64 db;\nmov.b64 db, {%40, %41};\n"
    "wgmma.mma_async.sync.aligned.m64n72k16.f32.bf16.bf16 {%0, %1, %2, %3, %4, %5, %6, %7, %8, %9, %10, %11, %12, %13, %14, %15, %16, %17, %18, %19, %20, %21, %22, %23, %24, %25, %26, %27, %28, %29, %30, %31, %32, %33, %34, %35}, {%36, %37, %38, %39}, db, 1, 1, 1, 0;\n}\n"
    : "+f"(d[0]), "+f"(d[1]), "+f"(d[2]), "+f"(d[3]), "+f"(d[4]), "+f"(d[5]), "+f"(d[6]), "+f"(d[7]), "+f"(d[8]), "+f"(d[9]), "+f"(d[10]), "+f"(d[11]), "+f"(d[12]), "+f"(d[13]), "+f"(d[14]), "+f"(d[15]), "+f"(d[16]), "+f"(d[17]), "+f"(d[18]), "+f"(d[19]), "+f"(d[20]), "+f"(d[21]), "+f"(d[22]), "+f"(d[23]), "+f"(d[24]), "+f"(d[25]), "+f"(d[26]), "+f"(d[27]), "+f"(d[28]), "+f"(d[29]), "+f"(d[30]), "+f"(d[31]), "+f"(d[32]), "+f"(d[33]), "+f"(d[34]), "+f"(d[35])
    : "r"(a[0]), "r"(a[1]), "r"(a[2]), "r"(a[3]), "r"(loH), "r"(hiH)
    : "memory");
}
template<> __device__ __forceinline__ void g1_step<10>(float* d, const uint32_t* a, uint32_t loH, uint32_t hiH) {
  asm volatile("{\n.reg .b64 db;\nmov.b64 db, {%44, %45};\n"
    "wgmma.mma_async.sync.aligned.m64n80k16.f32.bf16.bf16 {%0, %1, %2, %3, %4, %5, %6, %7, %8, %9, %10, %11, %12, %13, %14, %15, %16, %17, %18, %19, %20, %21, %22, %23, %24, %25, %26, %27, %28, %29, %30, %31, %32, %33, %34, %35, %36, %37, %38, %39}, {%40, %41, %42, %43}, db, 1, 1, 1, 0;\n}\n"
    : "+f"(d[0]), "+f"(d[1]), "+f"(d[2]), "+f"(d[3]), "+f"(d[4]), "+f"(d[5]), "+f"(d[6]), "+f"(d[7]), "+f"(d[8]), "+f"(d[9]), "+f"(d[10]), "+f"(d[11]), "+f"(d[12]), "+f"(d[13]), "+f"(d[14]), "+f"(d[15]), "+f"(d[16]), "+f"(d[17]), "+f"(d[18]), "+f"(d[19]), "+f"(d[20]), "+f"(d[21]), "+f"(d[22]), "+f"(d[23]), "+f"(d[24]), "+f"(d[25]), "+f"(d[26]), "+f"(d[27]), "+f"(d[28]), "+f"(d[29]), "+f"(d[30]), "+f"(d[31]), "+f"(d[32]), "+f"(d[33]), "+f"(d[34]), "+f"(d[35]), "+f"(d[36]), "+f"(d[37]), "+f"(d[38]), "+f"(d[39])
    : "r"(a[0]), "r"(a[1]), "r"(a[2]), "r"(a[3]), "r"(loH), "r"(hiH)
    : "memory");
}
template<> __device__ __forceinline__ void g1_step<11>(float* d, const uint32_t* a, uint32_t loH, uint32_t hiH) {
  asm volatile("{\n.reg .b64 db;\nmov.b64 db, {%48, %49};\n"
    "wgmma.mma_async.sync.aligned.m64n88k16.f32.bf16.bf16 {%0, %1, %2, %3, %4, %5, %6, %7, %8, %9, %10, %11, %12, %13, %14, %15, %16, %17, %18, %19, %20, %21, %22, %23, %24, %25, %26, %27, %28, %29, %30, %31, %32, %33, %34, %35, %36, %37, %38, %39, %40, %41, %42, %43}, {%44, %45, %46, %47}, db, 1, 1, 1, 0;\n}\n"
    : "+f"(d[0]), "+f"(d[1]), "+f"(d[2]), "+f"(d[3]), "+f"(d[4]), "+f"(d[5]), "+f"(d[6]), "+f"(d[7]), "+f"(d[8]), "+f"(d[9]), "+f"(d[10]), "+f"(d[11]), "+f"(d[12]), "+f"(d[13]), "+f"(d[14]), "+f"(d[15]), "+f"(d[16]), "+f"(d[17]), "+f"(d[18]), "+f"(d[19]), "+f"(d[20]), "+f"(d[21]), "+f"(d[22]), "+f"(d[23]), "+f"(d[24]), "+f"(d[25]), "+f"(d[26]), "+f"(d[27]), "+f"(d[28]), "+f"(d[29]), "+f"(d[30]), "+f"(d[31]), "+f"(d[32]), "+f"(d[33]), "+f"(d[34]), "+f"(d[35]), "+f"(d[36]), "+f"(d[37]), "+f"(d[38]), "+f"(d[39]), "+f"(d[40]), "+f"(d[41]), "+f"(d[42]), "+f"(d[43])
    : "r"(a[0]), "r"(a[1]), "r"(a[2]), "r"(a[3]), "r"(loH), "r"(hiH)
    : "memory");
}
template<> __device__ __forceinline__ void g1_step<12>(float* d, const uint32_t* a, uint32_t loH, uint32_t hiH) {
  asm volatile("{\n.reg .b64 db;\nmov.b64 db, {%52, %53};\n"
    "wgmma.mma_async.sync.aligned.m64n96k16.f32.bf16.bf16 {%0, %1, %2, %3, %4, %5, %6, %7, %8, %9, %10, %11, %12, %13, %14, %15, %16, %17, %18, %19, %20, %21, %22, %23, %24, %25, %26, %27, %28, %29, %30, %31, %32, %33, %34, %35, %36, %37, %38, %39, %40, %41, %42, %43, %44, %45, %46, %47}, {%48, %49, %50, %51}, db, 1, 1, 1, 0;\n}\n"
    : "+f"(d[0]), "+f"(d[1]), "+f"(d[2]), "+f"(d[3]), "+f"(d[4]), "+f"(d[5]), "+f"(d[6]), "+f"(d[7]), "+f"(d[8]), "+f"(d[9]), "+f"(d[10]), "+f"(d[11]), "+f"(d[12]), "+f"(d[13]), "+f"(d[14]), "+f"(d[15]), "+f"(d[16]), "+f"(d[17]), "+f"(d[18]), "+f"(d[19]), "+f"(d[20]), "+f"(d[21]), "+f"(d[22]), "+f"(d[23]), "+f"(d[24]), "+f"(d[25]), "+f"(d[26]), "+f"(d[27]), "+f"(d[28]), "+f"(d[29]), "+f"(d[30]), "+f"(d[31]), "+f"(d[32]), "+f"(d[33]), "+f"(d[34]), "+f"(d[35]), "+f"(d[36]), "+f"(d[37]), "+f"(d[38]), "+f"(d[39]), "+f"(d[40]), "+f"(d[41]), "+f"(d[42]), "+f"(d[43]), "+f"(d[44]), "+f"(d[45]), "+f"(d[46]), "+f"(d[47])
    : "r"(a[0]), "r"(a[1]), "r"(a[2]), "r"(a[3]), "r"(loH), "r"(hiH)
    : "memory");
}
__device__ __forceinline__ void g2_first(float (&o)[16], const uint32_t* a, uint32_t loH, uint32_t meta, uint32_t hiH) {
  asm volatile("{\n.reg .b64 db;\nmov.b64 db, {%20, %22};\n"
    "wgmma.mma_async.sp.sync.aligned.m64n32k32.f32.bf16.bf16 {%0, %1, %2, %3, %4, %5, %6, %7, %8, %9, %10, %11, %12, %13, %14, %15}, {%16, %17, %18, %19}, db, %21, 0, 0, 1, 1, 1;\n}\n"
    : "=f"(o[0]), "=f"(o[1]), "=f"(o[2]), "=f"(o[3]), "=f"(o[4]), "=f"(o[5]), "=f"(o[6]), "=f"(o[7]), "=f"(o[8]), "=f"(o[9]), "=f"(o[10]), "=f"(o[11]), "=f"(o[12]), "=f"(o[13]), "=f"(o[14]), "=f"(o[15])
    : "r"(a[0]), "r"(a[1]), "r"(a[2]), "r"(a[3]), "r"(loH), "r"(meta), "r"(hiH)
    : "memory");
}
__device__ __forceinline__ void g2_more(float (&o)[16], const uint32_t* a, uint32_t loH, uint32_t meta, uint32_t hiH) {
  asm volatile("{\n.reg .b64 db;\nmov.b64 db, {%20, %22};\n"
    "wgmma.mma_async.sp.sync.aligned.m64n32k32.f32.bf16.bf16 {%0, %1, %2, %3, %4, %5, %6, %7, %8, %9, %10, %11, %12, %13, %14, %15}, {%16, %17, %18, %19}, db, %21, 0, 1, 1, 1, 1;\n}\n"
    : "+f"(o[0]), "+f"(o[1]), "+f"(o[2]), "+f"(o[3]), "+f"(o[4]), "+f"(o[5]), "+f"(o[6]), "+f"(o[7]), "+f"(o[8]), "+f"(o[9]), "+f"(o[10]), "+f"(o[11]), "+f"(o[12]), "+f"(o[13]), "+f"(o[14]), "+f"(o[15])
    : "r"(a[0]), "r"(a[1]), "r"(a[2]), "r"(a[3]), "r"(loH), "r"(meta), "r"(hiH)
    : "memory");
}
template<int N> __device__ __forceinline__ void mma_wait(float* d, Int<4>) {
  asm volatile("wgmma.wait_group.sync.aligned %16;"
    : "+f"(d[0]), "+f"(d[1]), "+f"(d[2]), "+f"(d[3]), "+f"(d[4]), "+f"(d[5]), "+f"(d[6]), "+f"(d[7]), "+f"(d[8]), "+f"(d[9]), "+f"(d[10]), "+f"(d[11]), "+f"(d[12]), "+f"(d[13]), "+f"(d[14]), "+f"(d[15])
    : "n"(N) : "memory");
}
template<int N> __device__ __forceinline__ void mma_wait(float* d, Int<8>) {
  asm volatile("wgmma.wait_group.sync.aligned %32;"
    : "+f"(d[0]), "+f"(d[1]), "+f"(d[2]), "+f"(d[3]), "+f"(d[4]), "+f"(d[5]), "+f"(d[6]), "+f"(d[7]), "+f"(d[8]), "+f"(d[9]), "+f"(d[10]), "+f"(d[11]), "+f"(d[12]), "+f"(d[13]), "+f"(d[14]), "+f"(d[15]), "+f"(d[16]), "+f"(d[17]), "+f"(d[18]), "+f"(d[19]), "+f"(d[20]), "+f"(d[21]), "+f"(d[22]), "+f"(d[23]), "+f"(d[24]), "+f"(d[25]), "+f"(d[26]), "+f"(d[27]), "+f"(d[28]), "+f"(d[29]), "+f"(d[30]), "+f"(d[31])
    : "n"(N) : "memory");
}
template<int N> __device__ __forceinline__ void mma_wait(float* d, Int<9>) {
  asm volatile("wgmma.wait_group.sync.aligned %36;"
    : "+f"(d[0]), "+f"(d[1]), "+f"(d[2]), "+f"(d[3]), "+f"(d[4]), "+f"(d[5]), "+f"(d[6]), "+f"(d[7]), "+f"(d[8]), "+f"(d[9]), "+f"(d[10]), "+f"(d[11]), "+f"(d[12]), "+f"(d[13]), "+f"(d[14]), "+f"(d[15]), "+f"(d[16]), "+f"(d[17]), "+f"(d[18]), "+f"(d[19]), "+f"(d[20]), "+f"(d[21]), "+f"(d[22]), "+f"(d[23]), "+f"(d[24]), "+f"(d[25]), "+f"(d[26]), "+f"(d[27]), "+f"(d[28]), "+f"(d[29]), "+f"(d[30]), "+f"(d[31]), "+f"(d[32]), "+f"(d[33]), "+f"(d[34]), "+f"(d[35])
    : "n"(N) : "memory");
}
template<int N> __device__ __forceinline__ void mma_wait(float* d, Int<10>) {
  asm volatile("wgmma.wait_group.sync.aligned %40;"
    : "+f"(d[0]), "+f"(d[1]), "+f"(d[2]), "+f"(d[3]), "+f"(d[4]), "+f"(d[5]), "+f"(d[6]), "+f"(d[7]), "+f"(d[8]), "+f"(d[9]), "+f"(d[10]), "+f"(d[11]), "+f"(d[12]), "+f"(d[13]), "+f"(d[14]), "+f"(d[15]), "+f"(d[16]), "+f"(d[17]), "+f"(d[18]), "+f"(d[19]), "+f"(d[20]), "+f"(d[21]), "+f"(d[22]), "+f"(d[23]), "+f"(d[24]), "+f"(d[25]), "+f"(d[26]), "+f"(d[27]), "+f"(d[28]), "+f"(d[29]), "+f"(d[30]), "+f"(d[31]), "+f"(d[32]), "+f"(d[33]), "+f"(d[34]), "+f"(d[35]), "+f"(d[36]), "+f"(d[37]), "+f"(d[38]), "+f"(d[39])
    : "n"(N) : "memory");
}
template<int N> __device__ __forceinline__ void mma_wait(float* d, Int<11>) {
  asm volatile("wgmma.wait_group.sync.aligned %44;"
    : "+f"(d[0]), "+f"(d[1]), "+f"(d[2]), "+f"(d[3]), "+f"(d[4]), "+f"(d[5]), "+f"(d[6]), "+f"(d[7]), "+f"(d[8]), "+f"(d[9]), "+f"(d[10]), "+f"(d[11]), "+f"(d[12]), "+f"(d[13]), "+f"(d[14]), "+f"(d[15]), "+f"(d[16]), "+f"(d[17]), "+f"(d[18]), "+f"(d[19]), "+f"(d[20]), "+f"(d[21]), "+f"(d[22]), "+f"(d[23]), "+f"(d[24]), "+f"(d[25]), "+f"(d[26]), "+f"(d[27]), "+f"(d[28]), "+f"(d[29]), "+f"(d[30]), "+f"(d[31]), "+f"(d[32]), "+f"(d[33]), "+f"(d[34]), "+f"(d[35]), "+f"(d[36]), "+f"(d[37]), "+f"(d[38]), "+f"(d[39]), "+f"(d[40]), "+f"(d[41]), "+f"(d[42]), "+f"(d[43])
    : "n"(N) : "memory");
}
template<int N> __device__ __forceinline__ void mma_wait(float* d, Int<12>) {
  asm volatile("wgmma.wait_group.sync.aligned %48;"
    : "+f"(d[0]), "+f"(d[1]), "+f"(d[2]), "+f"(d[3]), "+f"(d[4]), "+f"(d[5]), "+f"(d[6]), "+f"(d[7]), "+f"(d[8]), "+f"(d[9]), "+f"(d[10]), "+f"(d[11]), "+f"(d[12]), "+f"(d[13]), "+f"(d[14]), "+f"(d[15]), "+f"(d[16]), "+f"(d[17]), "+f"(d[18]), "+f"(d[19]), "+f"(d[20]), "+f"(d[21]), "+f"(d[22]), "+f"(d[23]), "+f"(d[24]), "+f"(d[25]), "+f"(d[26]), "+f"(d[27]), "+f"(d[28]), "+f"(d[29]), "+f"(d[30]), "+f"(d[31]), "+f"(d[32]), "+f"(d[33]), "+f"(d[34]), "+f"(d[35]), "+f"(d[36]), "+f"(d[37]), "+f"(d[38]), "+f"(d[39]), "+f"(d[40]), "+f"(d[41]), "+f"(d[42]), "+f"(d[43]), "+f"(d[44]), "+f"(d[45]), "+f"(d[46]), "+f"(d[47])
    : "n"(N) : "memory");
}

__device__ __forceinline__ uint32_t smem_u32(const void* p) { return (uint32_t)__cvta_generic_to_shared(p); }

__device__ __forceinline__ void mbar_init(uint32_t bar, uint32_t cnt) {
  asm volatile("mbarrier.init.shared::cta.b64 [%0], %1;" :: "r"(bar), "r"(cnt) : "memory");
}
__device__ __forceinline__ void mbar_arrive(uint32_t bar) {
  asm volatile("mbarrier.arrive.shared::cta.b64 _, [%0];" :: "r"(bar) : "memory");
}
__device__ __forceinline__ void mbar_wait(uint32_t bar, uint32_t parity) {
  asm volatile("{\n.reg .pred p;\n.reg .u32 n;\n"
               "mov.u32 n, 0;\n"
               "WAIT_LOOP:\n"
               "mbarrier.try_wait.parity.shared::cta.b64 p, [%0], %1;\n"
               "@p bra.uni WAIT_DONE;\n"
               "add.u32 n, n, 1;\n"
               "setp.lt.u32 p, n, 0x1000000;\n"
               "@p bra.uni WAIT_LOOP;\n"
               "trap;\n"
               "WAIT_DONE:\n}\n"
               :: "r"(bar), "r"(parity) : "memory");
}
__device__ __forceinline__ uint32_t mbar_test(uint32_t bar, uint32_t parity) {
  uint32_t ok;
  asm volatile("{\n.reg .pred p;\nmbarrier.test_wait.parity.shared::cta.b64 p, [%1], %2;\nselp.u32 %0, 1, 0, p;\n}\n"
               : "=r"(ok) : "r"(bar), "r"(parity) : "memory");
  return ok;
}
__device__ __forceinline__ void cp_async16(uint32_t dst, const void* src) {
  asm volatile("cp.async.cg.shared.global [%0], [%1], 16;" :: "r"(dst), "l"(src) : "memory");
}
template<int T, int I, bool Z>
__device__ __forceinline__ void cp_row(uint32_t dst, uint64_t& a, uint32_t rows4, uint32_t base, int left, uint64_t pol) {
#define DIN_ADDR "mov.b64 {x, y}, %0;\ndp4a.u32.u32 x, %2, %8, %5;\nmov.b64 %0, {x, y};\n"
  if (Z)
    asm volatile("{\n.reg .u32 x, y;\n.reg .pred p;\n" DIN_ADDR "setp.le.s32 p, %6, %7;\n"
                 "cp.async.cg.shared.global.L2::cache_hint [%1 + %4], [%0], 16, p, %3;\n}\n"
                 : "+l"(a) : "r"(dst), "r"(rows4), "l"(pol), "n"(T * 2048), "r"(base), "r"(left), "n"(T * 16 + I), "n"(0x80u << 8 * I) : "memory");
  else
    asm volatile("{\n.reg .u32 x, y;\n" DIN_ADDR
                 "cp.async.cg.shared.global.L2::cache_hint [%1 + %4], [%0], 16, %3;\n}\n"
                 : "+l"(a) : "r"(dst), "r"(rows4), "l"(pol), "n"(T * 2048), "r"(base), "r"(left), "n"(T * 16 + I), "n"(0x80u << 8 * I) : "memory");
}
template<int T, bool Z>
__device__ __forceinline__ void cp_group(const uint32_t (&dst)[4], uint64_t& a, uint32_t rows4, uint32_t base, int left, uint64_t pol) {
  cp_row<T, 0, Z>(dst[0], a, rows4, base, left, pol);
  cp_row<T, 1, Z>(dst[1], a, rows4, base, left, pol);
  cp_row<T, 2, Z>(dst[2], a, rows4, base, left, pol);
  cp_row<T, 3, Z>(dst[3], a, rows4, base, left, pol);
}
__device__ __forceinline__ uint32_t prmt(uint32_t a, uint32_t b, uint32_t sel) {
  uint32_t d;
  asm("prmt.b32 %0, %1, %2, %3;" : "=r"(d) : "r"(a), "r"(b), "r"(sel));
  return d;
}
__device__ __forceinline__ uint32_t ballot_bit(uint32_t x, uint32_t bit) {
  uint32_t d;
  asm volatile("{\n.reg .pred p;\n.reg .u32 t;\nand.b32 t, %1, %2;\nsetp.ne.u32 p, t, 0;\nvote.sync.ballot.b32 %0, p, 0xffffffff;\n}\n"
               : "=r"(d) : "r"(x), "r"(bit));
  return d;
}
__device__ __forceinline__ uint4 load_mask(const void* mask, uint32_t b, uint32_t i) {
  uint4 m;
  asm volatile("ld.global.nc.L1::no_allocate.v4.u32 {%0,%1,%2,%3}, [%4];"
               : "=r"(m.x), "=r"(m.y), "=r"(m.z), "=r"(m.w) : "l"(reinterpret_cast<const uint4*>(mask) + (b * 25u + i)));
  return m;
}
__device__ __forceinline__ uint32_t nonzero_as_one(uint32_t x) {
  uint32_t d;
  asm("set.neu.bf16x2.bf16x2 %0, %1, %2;" : "=r"(d) : "r"(x), "r"(0u));
  return d;
}
__device__ __forceinline__ void cp_async_arrive_noinc(uint32_t bar) {
  asm volatile("cp.async.mbarrier.arrive.noinc.shared::cta.b64 [%0];" :: "r"(bar) : "memory");
}
__device__ __forceinline__ void ldsm_x4(uint32_t addr, uint32_t& r0, uint32_t& r1, uint32_t& r2, uint32_t& r3) {
  asm volatile("ldmatrix.sync.aligned.m8n8.x4.shared.b16 {%0,%1,%2,%3}, [%4];"
               : "=r"(r0), "=r"(r1), "=r"(r2), "=r"(r3) : "r"(addr) : "memory");
}
__device__ __forceinline__ void ldsm_x4_t(uint32_t addr, uint32_t& r0, uint32_t& r1, uint32_t& r2, uint32_t& r3) {
  asm volatile("ldmatrix.sync.aligned.m8n8.x4.trans.shared.b16 {%0,%1,%2,%3}, [%4];"
               : "=r"(r0), "=r"(r1), "=r"(r2), "=r"(r3) : "r"(addr) : "memory");
}
__device__ __forceinline__ void stsm_x4_t(uint32_t addr, uint32_t r0, uint32_t r1, uint32_t r2, uint32_t r3) {
  asm volatile("stmatrix.sync.aligned.m8n8.x4.trans.shared.b16 [%0], {%1,%2,%3,%4};"
               :: "r"(addr), "r"(r0), "r"(r1), "r"(r2), "r"(r3) : "memory");
}
__device__ __forceinline__ uint32_t hfma2_bf16(uint32_t a, uint32_t b, uint32_t c) {
  uint32_t d;
  asm volatile("fma.rn.bf16x2 %0, %1, %2, %3;" : "=r"(d) : "r"(a), "r"(b), "r"(c));
  return d;
}
__device__ __forceinline__ uint32_t pack_bf16(float lo, float hi) {
  uint32_t d;
  asm("cvt.rn.bf16x2.f32 %0, %1, %2;" : "=r"(d) : "f"(hi), "f"(lo));
  return d;
}
__device__ __forceinline__ uint32_t lds32(uint32_t a) {
  uint32_t v; asm volatile("ld.shared.u32 %0, [%1];" : "=r"(v) : "r"(a) : "memory"); return v;
}
__device__ __forceinline__ uint32_t lds16(uint32_t a) {
  uint32_t v; asm volatile("ld.shared.u16 %0, [%1];" : "=r"(v) : "r"(a) : "memory"); return v;
}
__device__ __forceinline__ void sts32(uint32_t a, uint32_t v) {
  asm volatile("st.shared.u32 [%0], %1;" :: "r"(a), "r"(v) : "memory");
}
__device__ __forceinline__ void sts16(uint32_t a, uint32_t v) {
  asm volatile("st.shared.u16 [%0], %1;" :: "r"(a), "h"((unsigned short)v) : "memory");
}
__device__ __forceinline__ void sts8(uint32_t a, uint32_t v) {
  asm volatile("st.shared.u8 [%0], %1;" :: "r"(a), "r"(v) : "memory");
}
constexpr uint32_t DESC_ROWS = 0x40000040u, DESC_HALVES = 0x80000020u;
__device__ __forceinline__ uint32_t desc_lo(uint32_t addr) { return ((addr & 0x3FFFF) >> 4) | (1u << 16); }

__device__ __forceinline__ uint4 lds128(uint32_t a) {
  uint4 v;
  asm volatile("ld.shared.v4.u32 {%0,%1,%2,%3}, [%4];" : "=r"(v.x), "=r"(v.y), "=r"(v.z), "=r"(v.w) : "r"(a) : "memory");
  return v;
}
__device__ __forceinline__ void sts128(uint32_t a, uint4 v) {
  asm volatile("st.shared.v4.u32 [%0], {%1,%2,%3,%4};" :: "r"(a), "r"(v.x), "r"(v.y), "r"(v.z), "r"(v.w) : "memory");
}
__device__ __forceinline__ void prefetch_l2(const void* p, uint32_t bytes) {
  asm volatile("cp.async.bulk.prefetch.L2.global [%0], %1;" :: "l"(p), "r"(bytes) : "memory");
}

__device__ __forceinline__ void cut_here(uint32_t& any, uint32_t zero) {
  asm volatile("{\n.reg .pred p;\nsetp.ne.u32 p, %1, 0;\n@p mov.u32 %0, %%clock;\n}\n" : "+r"(any) : "r"(zero) : "memory");
}
__device__ __forceinline__ void mma_fence() { asm volatile("wgmma.fence.sync.aligned;" ::: "memory"); }
__device__ __forceinline__ void mma_commit() { asm volatile("wgmma.commit_group.sync.aligned;" ::: "memory"); }
template<bool FIRST>
__device__ __forceinline__ void hmma(float (&c)[4], const uint32_t* a, uint32_t b0, uint32_t b1) {
  if (FIRST)
    asm volatile("mma.sync.aligned.m16n8k16.row.col.f32.bf16.bf16.f32 {%0,%1,%2,%3}, {%4,%5,%6,%7}, {%8,%9}, {%10,%10,%10,%10};"
                 : "=f"(c[0]), "=f"(c[1]), "=f"(c[2]), "=f"(c[3]) : "r"(a[0]), "r"(a[1]), "r"(a[2]), "r"(a[3]), "r"(b0), "r"(b1), "f"(0.f));
  else
    asm volatile("mma.sync.aligned.m16n8k16.row.col.f32.bf16.bf16.f32 {%0,%1,%2,%3}, {%4,%5,%6,%7}, {%8,%9}, {%0,%1,%2,%3};"
                 : "+f"(c[0]), "+f"(c[1]), "+f"(c[2]), "+f"(c[3]) : "r"(a[0]), "r"(a[1]), "r"(a[2]), "r"(a[3]), "r"(b0), "r"(b1));
}
__device__ __forceinline__ void tanh_some(float* d, int i0, int i1) {
#pragma unroll
  for (int i = i0; i < i1; i++) asm volatile("tanh.approx.f32 %0, %0;" : "+f"(d[i ^ 2]));
}
__device__ __forceinline__ uint32_t mix(const float* d, int i, float r) {
  uint32_t p;
  asm volatile("{\n.reg .f32 x, y;\nfma.rn.f32 x, %3, %5, %1;\nfma.rn.f32 y, %4, %5, %2;\ncvt.rn.bf16x2.f32 %0, y, x;\n}\n"
               : "=r"(p) : "f"(d[4 * i]), "f"(d[4 * i + 1]), "f"(d[4 * i + 2]), "f"(d[4 * i + 3]), "f"(r));
  return p;
}
__device__ __forceinline__ uint32_t sums_at(uint32_t d) { return S_OUT + (d ^ ((d >> 3) & 1)) * 16; }
template<int K> __device__ __forceinline__ uint32_t keep(uint32_t x) { return K ? __shfl_sync(0xffffffffu, x, 0) : x; }

template<int PF_M, int PF_T>
__global__ void __launch_bounds__(NTHREADS, 1)
din_kernel(const __nv_bfloat16* __restrict__ mask, const __nv_bfloat16* __restrict__ target, int B, int grid,
           const __nv_bfloat16* __restrict__ w1, const __nv_bfloat16* __restrict__ hist,
           const __nv_bfloat16* __restrict__ b1, const __nv_bfloat16* __restrict__ w2,
           const __nv_bfloat16* __restrict__ b2, __nv_bfloat16* __restrict__ out, unsigned int* counter, int pace16,
           int slow_pace, int slow_from) {
  const uint32_t tid = threadIdx.x, pf_at = blockIdx.x * NTHREADS + tid;
  asm volatile("{\n.reg .pred p;\nprefetch.global.L2 [%0];\nsetp.gt.u32 p, %1, 0x7ffffff0;\n@p exit;\n}\n"
               :: "l"(reinterpret_cast<const char*>(mask) + (size_t)pf_at * PF_M), "r"(blockIdx.x) : "memory");
  asm volatile("prefetch.global.L2 [%0];" :: "l"(reinterpret_cast<const char*>(target) + (size_t)pf_at * PF_T));
  extern __shared__ unsigned char smem_raw[];
  const uint32_t sb = (smem_u32(smem_raw) + 1023u) & ~1023u;
  const int lane = tid & 31;
  const uint32_t gwarp = __shfl_sync(0xffffffffu, pf_at >> 5, 0), cta = gwarp / (NTHREADS / 32);
  const int warp = gwarp % (NTHREADS / 32);
#define ACT NCW
  const int bstep = ACT * grid;

  if (warp < NCW * 4) {
    const int wg = warp >> 2, w = warp & 3;
    const int g = lane >> 2;
    const uint32_t ring = sb + wg * RING_BYTES;
    const bool active = wg * grid + (int)cta < B && wg < ACT;
    {
      const int t = tid & 127;
      const uint32_t dst = sb + ((t ^ ((t >> 3) & 7)) << 4);
      const char* src = reinterpret_cast<const char*>(w1) + t * 16;
#pragma unroll
      for (int i = 0; i < 4; i++) cp_async16(dst + w1_at(i) + wg * 2048, src + i * 8192 + wg * 2048);
      cp_async16(dst + w1_at(0) + wg * 8192 + 6144, src + wg * 8192 + 6144);
      if (wg == 0) cp_async16(dst + w1_at(3) + 6144, src + 3 * 8192 + 6144);
      if (lane < 8) {
        if (w == 0 && active) cp_async16(ring + R_TGT0 + lane * 16, target + (size_t)(wg * grid + cta) * kD + lane * 8);
        if (w == 1 && wg < 2) cp_async16(ring + R_VEC + lane * 16, (wg ? w2 : b1) + lane * 8);
      }
    }
    if (w == 2) sts32(ring + R_SEL + lane * 4, 0x3e803e80u);
    uint32_t rb2;
    asm volatile("ld.global.nc.u16 %0, [%1];" : "=r"(rb2) : "l"(b2));
    asm volatile("setmaxnreg.inc.sync.aligned.u32 %0;" :: "n"(CONS_REGS));
    asm volatile("cp.async.wait_all;" ::: "memory");
    asm volatile("bar.sync 1, %0;" :: "n"(NCW * 160) : "memory");
    float r;
    uint32_t cq, swap, half2, bf[4];
    {
      const uint32_t v2 = sb + RING_BYTES + R_VEC + ((lane & 24) * 2 + (lane & 7)) * 2;
      const float x = __uint_as_float(lds16(v2) << 16), y = __uint_as_float(lds16(v2 + 16) << 16);
      float c = x + y;
#pragma unroll
      for (int o = 16; o; o >>= 1) c += __shfl_xor_sync(0xffffffffu, c, o);
      c = 0.5f * c + __uint_as_float(rb2 << 16);
      const bool sw = fabsf(y) > fabsf(x);
      const float u = sw ? y : x, v = sw ? x : y;
      const bool off = !(fabsf(u) > fabsf(c) * 0x1p-40f);
      const float sc = off ? __uint_as_float(max(__float_as_uint(c) & 0x7f800000u, 8u << 23) - (4u << 23)) : 0.5f * u;
      float upto = fabsf(sc);
#pragma unroll
      for (int o = 2; o < 32; o *= 2) {
        const float z = __shfl_up_sync(0xffffffffu, upto, o);
        if (lane >= o) upto += z;
      }
      const float all = __shfl_sync(0xffffffffu, upto, 30 + (lane & 1));
      const float m = c / all;
      const float grid_ = __uint_as_float((__float_as_uint(2.0625f + 1.03125f * fabsf(m)) & 0x7f800000u) - (7u << 23));
      const float m0 = __fadd_rn(__fadd_rn(m, grid_ * 0x1.8p23f), grid_ * -0x1.8p23f);
      const float rest = fmaf(-m0, all, c);
      float q = (upto - 0.5f * fabsf(sc)) * grid_ < fabsf(rest) ? m0 + copysignf(grid_, rest) : m0;
      if (sc < 0.f) q = -q;
      const int own = 8 * w + g;
      r = __shfl_sync(0xffffffffu, off ? 0.f : v / u, own);
      cq = __shfl_sync(0xffffffffu, pack_bf16(q, q), own);
      swap = __shfl_sync(0xffffffffu, sw, own);
      half2 = __shfl_sync(0xffffffffu, off ? 0u : 0x3f003f00u, own);
      const int odd = (g ^ (g >> 1)) & 1;
#pragma unroll
      for (int i = 0; i < 4; i++)
        bf[i] = (__float_as_uint(__shfl_sync(0xffffffffu, sc, 8 * i + 2 * (lane & 3) + odd)) >> 16) << (16 * odd);
      if (warp == 0) {
        sts128(sb + SCALES + lane * 16, make_uint4(bf[0], bf[1], bf[2], bf[3]));
        asm volatile("bar.arrive 6, 160;" ::: "memory");
      }
    }
    const uint32_t nhalf2 = half2 ^ 0x80008000u, nzero2 = 0x80008000u;
    const uint32_t vec = sb + R_VEC + (16 * w + g) * 2;
    const float b1a = __uint_as_float(half2 << 16) * __uint_as_float(lds16(vec + (swap ? 16 : 0)) << 16);
    const float b1b = __uint_as_float(half2 << 16) * __uint_as_float(lds16(vec + (swap ? 0 : 16)) << 16);
    uint32_t wac[16], wd[16], wbc[16];
    {
      const int mi = lane >> 3, rr = lane & 7;
      const uint32_t a0 = sb + (8 * (mi >> 1) + rr) * 128 + (((2 * w + (mi & 1)) ^ rr) << 4);
#pragma unroll
      for (int ks = 0; ks < 4; ks++) {
        uint32_t A[4], Bm[4], C[4], Dm[4];
        ldsm_x4_t(a0 + ks * 2048 + w1_at(0), A[0], A[1], A[2], A[3]);
        ldsm_x4_t(a0 + ks * 2048 + w1_at(1), Bm[0], Bm[1], Bm[2], Bm[3]);
        ldsm_x4_t(a0 + ks * 2048 + w1_at(2), C[0], C[1], C[2], C[3]);
        ldsm_x4_t(a0 + ks * 2048 + w1_at(3), Dm[0], Dm[1], Dm[2], Dm[3]);
#pragma unroll
        for (int e = 0; e < 4; e++) {
          A[e] = hfma2_bf16(A[e], half2, hfma2_bf16(C[e], half2, nzero2));
          Bm[e] = hfma2_bf16(Bm[e], half2, hfma2_bf16(C[e], nhalf2, nzero2));
          Dm[e] = hfma2_bf16(Dm[e], half2, nzero2);
        }
#pragma unroll
        for (int e = 0; e < 4; e++) {
          wac[4 * ks + e] = swap ? A[e ^ 1] : A[e];
          wbc[4 * ks + e] = swap ? Bm[e ^ 1] : Bm[e];
          wd[4 * ks + e] = swap ? Dm[e ^ 1] : Dm[e];
        }
      }
    }
    asm volatile("fence.proxy.async.shared::cta;" ::: "memory");
    asm volatile("bar.sync 5, %0;" :: "n"(NCW * 128) : "memory");

    const uint32_t lnd = __shfl_sync(0xffffffffu, lane * 4 + ((8 * w + g + (lane & 1) * 32) << 25), lane);
    const uint32_t meta = __shfl_sync(0xffffffffu, g & 1 ? 0xdd8888ddu : 0x88dddd88u, lane);
    const uint32_t zr = grid >> 20;
    const uint32_t sel = keep<K_SEL>(((ring + R_SEL) & 0x3FFFF) >> 4);
    const uint32_t rat = __shfl_sync(0xffffffffu, sums_at(8 * w + (lane & 7)) + (lane >> 3) * 512, lane);
    const uint32_t barid = __shfl_sync(0xffffffffu, 2 + (tid >> 7), lane);
    const uint32_t toff = __shfl_sync(0xffffffffu, (lane & 24) << 1, lane);
    const uint32_t ost = __shfl_sync(0xffffffffu, w * 1024 + sums_at(lane), lane);
    if (active) {
      uint32_t t[8];
      auto load_t = [&](uint32_t ta) {
        ldsm_x4(ta + toff, t[0], t[1], t[2], t[3]);
        ldsm_x4(ta + toff + 64, t[4], t[5], t[6], t[7]);
      };
      load_t(ring + R_TGT0);
      uint32_t hdr = keep<1>(ring), raw, cur = hdr + (R_START - S_EMPTY);
      uint32_t x, nxt;
      auto peek_header = [&]() {
        nxt = hdr & H_NEXT;
        if (K_NX == 1) asm volatile("" : "+r"(nxt));
        x = lds32(nxt + S_HDR);
      };
      auto next_header = [&]() {
        asm volatile("{\n.reg .pred p;\n.reg .u32 n;\n.reg .s32 y;\n"
                     "xor.b32 y, %0, %2;\nsetp.ge.s32 p, y, 0;\n@p bra.uni FRESH;\n"
                     "mov.u32 n, 0;\n"
                     "AGAIN:\nadd.u32 n, n, 1;\nsetp.gt.u32 p, n, 0x1000000;\n@p trap;\nnanosleep.u32 32;\n"
                     "ld.volatile.shared.u32 %0, [%1];\nxor.b32 y, %0, %2;\nsetp.lt.s32 p, y, 0;\n@p bra.uni AGAIN;\n"
                     "FRESH:\n}\n" : "+r"(x) : "r"(nxt + S_HDR), "r"(hdr << 1) : "memory");
        if (!K_TOP) raw = __shfl_sync(0xffffffffu, x, 0);
      };
      uint32_t u[8];
      auto gather = [&](auto copy) {
        asm volatile("bar.sync %8, 128;   // %10\n"
                     "ldmatrix.sync.aligned.m8n8.x4.shared.b16 {%0,%1,%2,%3}, [%9];\n"
                     "ldmatrix.sync.aligned.m8n8.x4.shared.b16 {%4,%5,%6,%7}, [%9 + 2048];"
                     : "=r"(u[0]), "=r"(u[1]), "=r"(u[2]), "=r"(u[3]), "=r"(u[4]), "=r"(u[5]), "=r"(u[6]), "=r"(u[7])
                     : "r"(K_BAR ? barid : 2 + wg), "r"(cur + rat), "n"(decltype(copy)::value) : "memory");
      };
      peek_header();
      next_header();
      while (true) {
        __syncwarp();
        if (!(lnd & 0x7c)) mbar_arrive(cur + S_EMPTY);
        cur = K_NX == 2 ? hdr & H_NEXT : nxt;
        hdr = K_TOP ? __shfl_sync(0xffffffffu, x, 0) : raw;
        uint32_t we[16], bq[4];
        {
          float c[4][4];
          asm volatile("mma.sync.aligned.m16n8k16.row.col.f32.bf16.bf16.f32 {%0,%1,%2,%3}, {%4,%5,%6,%7}, {%8,%9}, {%10,%11,%12,%13};"
                       : "=f"(c[0][0]), "=f"(c[0][1]), "=f"(c[0][2]), "=f"(c[0][3])
                       : "r"(wbc[0]), "r"(wbc[1]), "r"(wbc[2]), "r"(wbc[3]), "r"(t[0]), "r"(t[1]), "f"(b1a), "f"(r), "f"(b1b), "f"(__uint_as_float(cq)));
#pragma unroll
          for (int i = 1; i < 4; i++) hmma<true>(c[i], wbc + 4 * i, t[2 * i], t[2 * i + 1]);
#pragma unroll
          for (int i = 0; i < 16; i++) we[i] = hfma2_bf16(t[i >> 1], wd[i], wac[i]);
#pragma unroll
          for (int i = 0; i < 4; i++) bq[i] = pack_bf16(c[i & 2][2 * (i & 1)], c[(i & 2) + 1][2 * (i & 1)]);
        }
        auto chunk = [&](auto groups) {
          constexpr int N8 = decltype(groups)::value, KE = (N8 + 1) / 2, KA = KE - KL;
          float d[4 * N8], o[16];
          uint32_t a[4 * KE];
          auto scores = [&](int i0, int i1) {
#pragma unroll
            for (int i = i0; i < i1; i++) {
              a[2 * i] = i < N8 ? mix(d, i, r) : 0;
              a[2 * i + 1] = i < N8 ? hfma2_bf16(a[2 * i], 0x3f803f80u, cq) : 0;
              if (N8 == 16) {
                uint32_t m = 0x3f803f80u;
                asm volatile("{\n.reg .pred p;\nsetp.ne.u32 p, %1, 0;\n@p ld.shared.u32 %0, [%2];\n}\n"
                             : "+r"(m) : "r"(hdr & H_GENERAL), "r"(cur + S_MASK + i * 16 + (lnd & 12)) : "memory");
                a[2 * i] = hfma2_bf16(a[2 * i], m, 0x80008000u);
                a[2 * i + 1] = hfma2_bf16(a[2 * i + 1], m, 0x80008000u);
              }
            }
          };
          const uint32_t lo = cur >> 4, lo1 = lo + 0x10000, lo2 = lo + K_LO2 * 0x10000;
          const uint32_t hi1 = DESC_ROWS + (K_HI1 == 1 ? cur >> 24 : lo >> 19);
          const uint32_t hi2 = K_HI2 == 1 ? DESC_HALVES + (cur >> 24) : hi1 + (DESC_HALVES - DESC_ROWS);
          auto g2 = [&](int k) {
            if (k == 0) g2_first(o, a, lo2, meta, hi2); else g2_more(o, a + 4 * k, lo2 + 128 * k, meta, hi2);
          };
          uint32_t oa = cur + ost;
          mma_fence();
          g1_bias<NA>(d, bq, sel);
          g1_bias<N8 - NA>(d + 4 * NA, bq, sel);
          mma_commit();
          mbar_wait(cur + S_FULL, hdr >> 31);
          mma_fence();
#pragma unroll
          for (int k = 0; k < 4; k++) g1_step<NA>(d, we + 4 * k, lo1 + 2 * k, hi1);
          mma_commit();
#pragma unroll
          for (int k = 0; k < 4; k++) g1_step<N8 - NA>(d + 4 * NA, we + 4 * k, lo1 + 64 * NA + 2 * k, hi1);
          mma_commit();
          mma_wait<1>(d, Int<NA>());
          tanh_some(d, 0, 4 * NA);
          scores(0, S0);
          cut_here(oa, zr);
          mma_wait<0>(d + 4 * NA, Int<N8 - NA>());
          load_t(cur + S_TGT);
          peek_header();
          tanh_some(d, 4 * NA, 8 * KA + D0);
          scores(S0, 2 * KA);
          mma_fence();
#pragma unroll
          for (int k = 0; k < KA; k++) {
            g2(k);
            if (k == KA - KC) cut_here(oa, zr);
          }
          mma_commit();
          tanh_some(d, 8 * KA + D0, 4 * N8);
          scores(2 * KA, 2 * KE);
          mma_fence();
#pragma unroll
          for (int k = KA; k < KE; k++) g2(k);
          mma_commit();
          next_header();
          mma_wait<0>(o, Int<4>());
#pragma unroll
          for (int e = 0; e < 2; e++)
            stsm_x4_t(oa + e * 512, pack_bf16(o[2 * e], o[2 * e + 1]), pack_bf16(o[2 * e + 4], o[2 * e + 5]),
                      pack_bf16(o[2 * e + 8], o[2 * e + 9]), pack_bf16(o[2 * e + 12], o[2 * e + 13]));
        };
        if (hdr & H_13) { chunk(Int<13>()); if (hdr & (H_FINAL | H_12)) { gather(Int<0>()); break; } }
        else if (hdr & H_12) { chunk(Int<12>()); if (hdr & (H_FINAL | H_14)) { gather(Int<1>()); break; } }
        else if (hdr & H_14) { chunk(Int<14>()); if (hdr & (H_FINAL | H_15)) { gather(Int<2>()); break; } }
        else if (hdr & H_15) { chunk(Int<15>()); if (hdr & (H_FINAL | H_16)) { gather(Int<3>()); break; } }
        else {
          asm volatile("{\n.reg .pred p;\nsetp.ne.u32 p, %0, 0;\n@p exit;\n}\n" :: "r"(hdr & H_STOP) : "memory");
          chunk(Int<16>());
          if (hdr & H_FINAL) { gather(Int<4>()); break; }
        }
      }
      float c[4], e[4];
      hmma<true>(c, u, bf[0], bf[1]);
      hmma<true>(e, u + 4, bf[2], bf[3]);
      const char* dst = reinterpret_cast<const char*>(out) + (uint64_t)(x * 2) * kD + (lnd >> 24);
      asm volatile("st.global.u16 [%0], %1;"
                   :: "l"(dst), "h"(__bfloat16_as_ushort(__float2bfloat16((c[0] + c[3]) + (e[0] + e[3])))) : "memory");
      asm volatile("exit;");
    }
  } else {
    const int pw = warp - NCW * 4;
    const uint32_t ring = sb + pw * RING_BYTES;
    asm volatile("setmaxnreg.dec.sync.aligned.u32 %0;" :: "n"(PROD_REGS));
    if (pw < NCW) {
      int b = pw * grid + cta, bn = b + bstep;
      uint4 mw = load_mask(mask, min(b, B - 1), min(lane, 24));
      if (lane == 0) {
#pragma unroll
        for (int i = 0; i < NSLOT; i++) {
          mbar_init(ring + i * SLOT_BYTES + S_FULL, 34);
          mbar_init(ring + i * SLOT_BYTES + S_EMPTY, 4);
          mbar_arrive(ring + i * SLOT_BYTES + S_FULL);
          sts32(ring + i * SLOT_BYTES + S_HDR, 0x80000000u);
        }
        mbar_init(ring + R_START, 4);
        sts32(ring + R_STOP, pw < ACT ? 0 : ring);
      }
      sts32(sb + R_PACE + lane * 4, 0);
      asm volatile("bar.arrive 1, %0;" :: "n"(NCW * 160) : "memory");
      asm volatile("bar.arrive 6, 160;" ::: "memory");
      if (pw >= ACT) return;
      const uint32_t list = ring + R_LIST;
      uint32_t lt;
      asm("mov.u32 %0, %%lanemask_lt;" : "=r"(lt));
      const uint32_t ln = __shfl_sync(0xffffffffu, lane, lane);
      const uint32_t r4 = (ln >> 3) * 4, c16 = (ln & 7) * 16, l25 = min(ln, 24u);
      const uint32_t pick = ln < 25 ? 0xeca8 : 0x9999;
      uint32_t dst[4];
#pragma unroll
      for (int i = 0; i < 4; i++) dst[i] = ring + (r4 + i) * 128 + (c16 ^ (((r4 + i) & 7) << 4));
      uint64_t pol;
      asm("createpolicy.fractional.L2::evict_first.b64 %0, 1.0;" : "=l"(pol));
      uint32_t sa = ring, phase = 1;
      const uint32_t wrap = (uint32_t)(max(B - NSTATIC * bstep, 0) + bstep - 1);
      auto next_slot = [&]() {
        const bool wrapped = sa == ring + (NSLOT - 1) * SLOT_BYTES;
        const int step = wrapped ? -(NSLOT - 1) * SLOT_BYTES : SLOT_BYTES;
        sa += step;
        phase ^= wrapped;
#pragma unroll
        for (int i = 0; i < 4; i++) dst[i] += step;
      };
      uint32_t claimer = ln;
      uint32_t drawn;
      auto draw = [&]() {
        drawn = B;
        asm volatile("{\n.reg .pred p;\nsetp.eq.u32 p, %3, 0;\n@p atom.global.inc.u32 %0, [%1], %2;\n}\n"
                     : "+r"(drawn) : "l"(counter), "r"(wrap), "r"(claimer) : "memory");
      };
      if (b >= B) draw();
      int n = kL, mean16 = 8 * kL;
      while (b < B) {
        const uint32_t e0 = nonzero_as_one(mw.x), e1 = nonzero_as_one(mw.y);
        const uint32_t e2 = nonzero_as_one(mw.z), e3 = nonzero_as_one(mw.w);
        const uint32_t nonbin = (e0 ^ mw.x) | (e1 ^ mw.y) | (e2 ^ mw.z) | (e3 ^ mw.w);
        const uint32_t sA = prmt(e0, e1, pick), sB = prmt(e2, e3, pick);
        const uint32_t pA = (sA & 0x01010101u) * 0x01010101u;
        const uint32_t pB = ((sB & 0x01010101u) + (pA >> 24)) * 0x01010101u;
        uint32_t pos = 0;
        n = 0;
#pragma unroll
        for (int k = 0; k < 4; k++) {
          const uint32_t bal = ballot_bit(pB, 0x01000000u << k);
          pos += __popc(bal & lt) << k;
          n += __popc(bal) << k;
        }
        const uint32_t general = __any_sync(0xffffffffu, nonbin != 0);
        const uint32_t aA = (pA + pos * 0x01010101u) | ~sA, aB = (pB + pos * 0x01010101u) | ~sB;
#pragma unroll
        for (int i = 0; i < 8; i++) sts8(list - 1 + prmt(i < 4 ? aA : aB, 0, 0x4440 + (i & 3)), 8 * ln + i);
        __syncwarp();

        const uint64_t src = reinterpret_cast<uint64_t>(hist) + (uint64_t)b * (kL * kD * 2);
        const bool no_carry = (uint32_t)src <= 0xffffffffu - kL * kD * 2;
        auto begin_fill = [&](uint32_t h, uint32_t part, int nc, int bt, auto extra) {
          mbar_wait(sa + S_EMPTY, phase);
          if (bt >= B && !part) h |= H_FINAL;
          extra();
          {
            const bool wrapped = sa == ring + (NSLOT - 1) * SLOT_BYTES;
            sts32(sa + S_HDR, (h | (wrapped ? ring + 0x40000000u : sa + SLOT_BYTES)) ^ ((phase - 1) & 0xc0000000u));
          }
          sts32(sa + S_ROW + phase * 4, b | part);
          asm volatile("{\n.reg .pred p;\nsetp.eq.u32 p, %1, 0;\n@p mbarrier.arrive.shared::cta.b64 _, [%0];\n}\n"
                       :: "r"(sa + S_FULL), "r"(ln) : "memory");
          mean16 += nc - (mean16 >> 4);
          asm volatile("{\n.reg .u32 f, c;\n.reg .s32 d;\n.reg .pred p;\n"
                       "mov.u32 c, %%globaltimer_lo;\n"
                       "red.shared.max.u32 [%0], c;\n"
                       "atom.shared.add.u32 f, [%0], %1;\n"
                       "shfl.sync.idx.b32 f, f, 0, 31, 0xffffffff;\n"
                       "SPIN:\n"
                       "mov.u32 c, %%globaltimer_lo;\n"
                       "sub.s32 d, c, f;\n"
                       "setp.gt.u32 p, d, %2;\n"
                       "@p bra.uni SPIN;\n}\n" :: "r"(sb + R_PACE + ln * 4), "r"((bn >= slow_from ? mean16 * slow_pace : nc * pace16) >> 8), "r"(~(pace16 * (CHUNK / 64))) : "memory");
          if (!(part & ROW_REST)) {
            mw = load_mask(mask, min(bn, B - 1), l25);
            draw();
          }
          asm volatile("cp.async.ca.shared.global [%0], [%1], 4;"
                       :: "r"(sa + S_TGT + ln * 4), "l"(reinterpret_cast<const uint32_t*>(target) + ((uint32_t)min(bt, B - 1) * 32u + ln)) : "memory");
        };
        auto end_fill = [&](int nc) {
          cp_async_arrive_noinc(sa + S_FULL);
          next_slot();
        };
        auto usual = [&]() {
          uint32_t idx[7];
#pragma unroll
          for (int t = 0; t < 7; t++) idx[t] = lds32(list + r4 + t * 16);
          begin_fill(size_flag(n), 0, n, bn, [](){});
          const int left = n - r4;
          const uint32_t base = (uint32_t)src + c16;
          uint64_t a = (uint64_t)((uint32_t)(src >> 32) + (ln >> 5)) << 32;
          cp_group<0, false>(dst, a, idx[0], base, left, pol);
          cp_group<1, false>(dst, a, idx[1], base, left, pol);
          cp_group<2, false>(dst, a, idx[2], base, left, pol);
          cp_group<3, false>(dst, a, idx[3], base, left, pol);
          cp_group<4, true>(dst, a, idx[4], base, left, pol);
          cp_group<5, true>(dst, a, idx[5], base, left, pol);
          if (n > 96) {
            cp_group<6, true>(dst, a, idx[6], base, left, pol);
            if (n > 112) cp_group<7, true>(dst, a, lds32(list + r4 + 112), base, left, pol);
          }
          end_fill(n);
        };
        auto other = [&]() {
          int r0 = 0, nc = n <= CHUNK ? n : n <= 160 ? 64 : 96;
#pragma unroll 1
          do {
            const bool more = r0 + nc < n;
            begin_fill(general ? H_GENERAL : size_flag(max(nc, 64)), (more ? ROW_MORE : 0u) | (r0 ? ROW_REST : 0u), nc, more ? b : bn, [&]() {
#pragma unroll 1
              for (int z = ln; general && z < CHUNK; z += 32) {
                uint32_t v = 0;
                if (z < nc) {
                  uint32_t row;
                  asm volatile("ld.shared.u8 %0, [%1];" : "=r"(row) : "r"(list + r0 + z) : "memory");
                  v = __bfloat16_as_ushort(mask[(size_t)b * kL + row]);
                }
                sts16(sa + S_MASK + z * 2, v);
              }
              __syncwarp();
            });
            uint32_t rows4 = lds32(list + r0 + r4);
#pragma unroll 1
            for (int z = 0; z < (general ? CHUNK : max(nc, 96)); z += 16) {
              const uint32_t now = rows4;
              rows4 = lds32(list + r0 + r4 + z + 16);
#pragma unroll
              for (int i = 0; i < 4; i++)
                asm volatile("{\n.reg .pred p;\nsetp.ge.s32 p, %2, %3;\ncp.async.cg.shared.global.L2::cache_hint [%0], [%1], 16, p, %4;\n}\n"
                             :: "r"(dst[i] + z * 128), "l"(src + c16 + prmt(now, 0, 0x4440 + i) * 128), "r"(z + r4 + i), "r"(nc), "l"(pol) : "memory");
            }
            end_fill(nc);
            r0 += nc;
            nc = n - nc;
          } while (r0 < n);
        };
        if (n < 64 || n > CHUNK || !no_carry || general) other(); else usual();
        if (bn >= B) break;
        b = bn;
        bn = __shfl_sync(0xffffffffu, drawn, 0) + NSTATIC * bstep;
        if (bn >= B) claimer = 1;
      }
      if (b < B) mbar_wait(ring + R_START, 0);
      sts32(sa + S_HDR, (n <= CHUNK ? b : H_STOP) | (phase ^ 1) << 31);
      if (n <= CHUNK) {
#pragma unroll 1
        for (int i = 1; i < 2 * NSLOT; i++) next_slot();
      }
      sts32(ring + R_STOP, sa + (phase ^ 1));
      asm volatile("cp.async.wait_all;" ::: "memory");
    } else {
      uint32_t due = clock();
      int s0 = NSTATIC * bstep + (PF_EARLY * grid + cta) * PF_ROWS;
      auto prefetch = [&]() {
        const int cnt = min(PF_ROWS, B - s0);
        if (lane == 0) {
          prefetch_l2(mask + (size_t)s0 * kL, cnt * kL * 2);
          prefetch_l2(target + (size_t)s0 * kD, cnt * kD * 2);
        }
        s0 += grid * PF_ROWS;
      };
#pragma unroll 1
      for (int j = PF_EARLY; j < PF_FAST && s0 < B; j++) {
        while ((int)(due - (uint32_t)clock()) > 0) {}
        prefetch();
        due += PF_CYCLES;
      }
      due += (PF_FAST - 1) * PF_SLOW - (PF_FAST - PF_EARLY) * PF_CYCLES + (cta & 255) * (PF_SLOW / 256);
      asm volatile("bar.sync 6, 160;" ::: "memory");
      constexpr uint32_t WHERE = 0x3ffff;
      const uint32_t mine = __shfl_sync(0xffffffffu, sb + min(lane, NCW - 1) * RING_BYTES, lane);
      uint32_t at = mine | ~WHERE;
      const uint32_t ln = __shfl_sync(0xffffffffu, lane, lane);
      const uint32_t rd = __shfl_sync(0xffffffffu, sums_at(2 * (lane & 7)) + (lane >> 3) * 512, lane);
      uint4 bf = lds128(sb + SCALES + lane * 16);
      bf.x += grid >> 20;
      bf.z += grid >> 20;
      uint32_t* const dst = reinterpret_cast<uint32_t*>(out) + ((lane & 1) * 16 + (lane & 2) * 4 + (lane >> 2));
      uint32_t idle = 0;
#pragma unroll 1
      while (true) {
        const uint32_t go = __reduce_max_sync(0xffffffffu, mbar_test((at & (WHERE - 1)) + S_EMPTY, at & 1) ? at : 0u);
        if (go) {
          const uint32_t sa = go & (WHERE - 1);
          const uint32_t row = lds32(sa + S_ROW + 4 - (go & 1) * 4);
          uint32_t u[8][4];
#pragma unroll
          for (int i = 0; i < 8; i++) ldsm_x4(((sa + rd) ^ (i & 1) * 16) + (i & 2) * 128 + (i >> 2) * 2048, u[i][0], u[i][1], u[i][2], u[i][3]);
          cut_here(idle, sa == 0);
          float c[4][4];
#pragma unroll
          for (int j = 0; j < 4; j++) hmma<true>(c[j], u[j], bf.x, bf.y);
#pragma unroll
          for (int j = 0; j < 4; j++) hmma<false>(c[j], u[4 + j], bf.z, bf.w);
          float e0 = c[0][0] + c[0][3], e1 = c[1][0] + c[1][3];
          if (ln & 2) { e0 = c[2][0] + c[2][3]; e1 = c[3][0] + c[3][3]; }
          __syncwarp();
          if (ln == 0) mbar_arrive(sa + S_FULL);
          if (at == go) at = (sa == mine + (NSLOT - 1) * SLOT_BYTES ? (at - (NSLOT - 1) * SLOT_BYTES) ^ 1 : at + SLOT_BYTES) - (WHERE + 1);
          if (__builtin_expect(row >= ROW_REST, 0)) {
            const uint32_t carry = __reduce_max_sync(0xffffffffu, mine <= sa ? mine : 0u) + R_CARRY + ln * 8;
            if (row & ROW_REST) { e0 += __uint_as_float(lds32(carry)); e1 += __uint_as_float(lds32(carry + 4)); }
            sts32(carry, __float_as_uint(e0));
            sts32(carry + 4, __float_as_uint(e1));
          }
          if (row < ROW_MORE) dst[(row & (ROW_REST - 1)) * 32] = pack_bf16(e0, e1);
        } else {
          uint32_t stop;
          asm volatile("ld.volatile.shared.u32 %0, [%1];" : "=r"(stop) : "r"(mine + R_STOP) : "memory");
          if (__all_sync(0xffffffffu, stop == (at & WHERE))) break;
          if (++idle > 0x4000000) __trap();
          if (s0 < B && (int)(due - (uint32_t)clock()) <= 0) { prefetch(); due += PF_SLOW; }
          if (RED_SLEEP) __nanosleep(RED_SLEEP);
        }
      }
    }
  }
}

}

extern "C" void kernel_launch(void* const* d_in, const int* in_sizes, int n_in, void* d_out, int out_size) {
  const __nv_bfloat16* target = (const __nv_bfloat16*)d_in[0];
  const __nv_bfloat16* hist = (const __nv_bfloat16*)d_in[1];
  const __nv_bfloat16* mask = (const __nv_bfloat16*)d_in[2];
  const __nv_bfloat16* w1 = (const __nv_bfloat16*)d_in[3];
  const __nv_bfloat16* b1 = (const __nv_bfloat16*)d_in[4];
  const __nv_bfloat16* w2 = (const __nv_bfloat16*)d_in[5];
  const __nv_bfloat16* b2 = (const __nv_bfloat16*)d_in[6];
  const int B = in_sizes[0] / din::kD;
  if (B <= 0) return;
  constexpr int early_rows = din::NSTATIC * NCW + PF_EARLY * PF_ROWS;
  constexpr int pf_mask = (early_rows * din::kL * 2 + din::NTHREADS - 1) / din::NTHREADS;
  constexpr int pf_tgt = (early_rows * din::kD * 2 + din::NTHREADS - 1) / din::NTHREADS;
  static int sms = 0, pace = 0;
  static unsigned int* counter = nullptr;
  if (sms == 0) {
    int dev = 0, khz = 0, bits = 0;
    cudaGetDevice(&dev);
    cudaDeviceGetAttribute(&sms, cudaDevAttrMultiProcessorCount, dev);
    cudaDeviceGetAttribute(&khz, cudaDevAttrMemoryClockRate, dev);
    cudaDeviceGetAttribute(&bits, cudaDevAttrGlobalMemoryBusWidth, dev);
    if (khz > 0 && bits > 0) pace = (int)(16.0 * 128.0 * sms / (khz * 1e-6 * 2.0 * bits / 8.0));
    if (pace > 256) pace = 0;
    cudaGetSymbolAddress((void**)&counter, din::g_next);
    cudaFuncSetAttribute(din::din_kernel<0, 0>, cudaFuncAttributeMaxDynamicSharedMemorySize, din::SMEM_BYTES);
    cudaFuncSetAttribute(din::din_kernel<pf_mask, pf_tgt>, cudaFuncAttributeMaxDynamicSharedMemorySize, din::SMEM_BYTES);
  }
  const bool early = (long long)pf_mask * din::NTHREADS * sms <= (long long)B * din::kL * 2 &&
                     (long long)pf_tgt * din::NTHREADS * sms <= (long long)B * din::kD * 2;
  (early ? din::din_kernel<pf_mask, pf_tgt> : din::din_kernel<0, 0>)<<<sms, din::NTHREADS, din::SMEM_BYTES>>>(
      mask, target, B, sms, w1, hist, b1, w2, b2, (__nv_bfloat16*)d_out, counter, pace * 16,
      pace + pace * SLOW_BY / 80, B - SLOW_ROUNDS * NCW * sms);
}
```
